```python
import torch

def _softmax(x, axis=-1):
    return torch.softmax(x, dim=axis)

def _gelu(x):
    return torch.nn.functional.gelu(x, approximate='tanh')

def _silu(x):
    return torch.nn.functional.silu(x)

def _sigmoid(x):
    return torch.sigmoid(x)

def _layernorm(x, axis=-1, eps=1e-05):
    m = x.mean(dim=axis, keepdim=True)
    v = x.var(dim=axis, keepdim=True, unbiased=False)
    return (x - m) / torch.sqrt(v + eps)

def _scatter_add(tgt, idx, src, axis=0):
    return tgt.clone().index_add_(axis, idx, src)

def _segment_sum(src, seg, n):
    out = torch.zeros((n,) + src.shape[1:], dtype=src.dtype)
    return out.index_add_(0, seg, src)

def _pad(x, pw):
    flat = tuple((v for pair in reversed(pw) for v in pair))
    return torch.nn.functional.pad(x, flat)
kernel_name = 'parallel_sum__memory_aug_recurrent_mem_tr__glu_gated_bilinear__prompt'

def setup_inputs():

    _w = lambda a: (lambda t: t.to(torch.bfloat16) if t.is_floating_point() else t)(torch.as_tensor(a))

    def _A_setup():
        B, S, Dm = (1, 2048, 512)
        H, Dh = (32, 128)
        M, seg = (8, 32)
        seg = min(seg, S)
        S = S // seg * seg
        return {'x': _w((lambda *s: torch.randn(*s, dtype=torch.bfloat16) * 0.05)(B, S, Dm)), 'mem0': _w((lambda *s: torch.randn(*s, dtype=torch.bfloat16) * 0.2)(B, M, Dm)), 'Wq': _w((lambda *s: torch.randn(*s, dtype=torch.bfloat16) * 1.6)(Dm, H, Dh) * Dm ** (-0.5)), 'Wk': _w((lambda *s: torch.randn(*s, dtype=torch.bfloat16) * 1.6)(Dm, H, Dh) * Dm ** (-0.5)), 'Wv': _w((lambda *s: torch.randn(*s, dtype=torch.bfloat16) * 0.2)(Dm, H, Dh) * Dm ** (-0.5)), 'Wo': _w((lambda *s: torch.randn(*s, dtype=torch.bfloat16) * 0.2)(H, Dh, Dm) * (H * Dh) ** (-0.5)), 'seg_len': seg}
    _A_in = _A_setup()

    def _B_setup():
        B, S, D, F = (1, 2048, 512, 1376)
        return {'x': _w((lambda *s: torch.randn(*s, dtype=torch.bfloat16) * 0.05)(B, S, D)), 'w_gate': _w((lambda *s: torch.randn(*s, dtype=torch.bfloat16) * 0.2)(D, F) * D ** (-0.5)), 'w_up': _w((lambda *s: torch.randn(*s, dtype=torch.bfloat16) * 0.2)(D, F) * D ** (-0.5)), 'w_down': _w((lambda *s: torch.randn(*s, dtype=torch.bfloat16) * 0.2)(F, D) * F ** (-0.5))}
    _B_in = _B_setup()
    return {'A_x': _A_in['x'], 'A_mem0': _A_in['mem0'], 'A_Wq': _A_in['Wq'], 'A_Wk': _A_in['Wk'], 'A_Wv': _A_in['Wv'], 'A_Wo': _A_in['Wo'], 'A_seg_len': _A_in['seg_len'], 'B_x': _B_in['x'], 'B_w_gate': _B_in['w_gate'], 'B_w_up': _B_in['w_up'], 'B_w_down': _B_in['w_down']}

def reference(A_x, A_mem0, A_Wq, A_Wk, A_Wv, A_Wo, A_seg_len, B_x, B_w_gate, B_w_up, B_w_down):

    def _A_ref(x, mem0, Wq, Wk, Wv, Wo, seg_len):
        B, S, Dm = x.shape
        H, Dh = (Wq.shape[1], Wq.shape[2])
        M = mem0.shape[1]
        scale = Dh ** (-0.5)
        n_seg = S // seg_len
        L = M + seg_len
        idx = torch.arange(L)
        mask = (idx[:, None] < M) | (idx[:, None] >= idx[None, :])
        mem = mem0
        outs = []
        for s in range(n_seg):
            xs = x[:, s * seg_len:(s + 1) * seg_len, :].clone()
            h = torch.concatenate([mem, xs], axis=1)
            q = torch.einsum('btd,dhe->bhte', h, Wq)
            k = torch.einsum('btd,dhe->bhte', h, Wk)
            v = torch.einsum('btd,dhe->bhte', h, Wv)
            scores = torch.einsum('bhqe,bhke->bhqk', q, k) * scale
            scores = torch.where(mask[None, None], scores, -1000000000.0)
            p = _softmax(scores, axis=-1)
            o = torch.einsum('bhqk,bhke->bhqe', p, v)
            o = torch.einsum('bhte,hed->btd', o, Wo)
            mem = o[:, :M, :].clone()
            outs.append(o[:, M:, :])
        return torch.concatenate(outs, axis=1)

    def _B_ref(x, w_gate, w_up, w_down):
        g = torch.einsum('bsd,df->bsf', x, w_gate)
        u = torch.einsum('bsd,df->bsf', x, w_up)
        h = g * u
        return torch.einsum('bsf,fd->bsd', h, w_down)
    x = A_x
    xn = _layernorm(x, axis=-1)
    return x + _A_ref(xn, A_mem0, A_Wq, A_Wk, A_Wv, A_Wo, A_seg_len) + _B_ref(xn, B_w_gate, B_w_up, B_w_down)
```

```cpp
#include <cuda_runtime.h>
#include <cuda_bf16.h>
#include <cuda.h>
#include <stdint.h>

namespace {

constexpr int S_TOK = 2048, DM = 512, NH = 32, DH = 128, NSEG = 64, FF = 1376;
constexpr int NCL = 16, CLS = 6;
constexpr int NVST = 4;
constexpr int HCH = 22;

__device__ __align__(1024) unsigned char g_xn[8 * S_TOK * 128];
__device__ __align__(1024) unsigned char g_ox[64 * S_TOK * 128];
__device__ __align__(1024) unsigned char g_h[HCH * S_TOK * 128];
__device__ __align__(1024) unsigned char g_q[8 * NH * 8192];
__device__ __align__(1024) unsigned char g_k[8 * NH * 8192];
__device__ __align__(1024) unsigned char g_v[4 * NCL * 16384];
constexpr int EX_RANK = 12 * 2048, EX_BUF = CLS * EX_RANK;
__device__ __align__(1024) unsigned char g_ex[4 * EX_BUF];
__device__ unsigned int g_cnt[NSEG];
__device__ unsigned int g_hcnt[16];
__device__ unsigned int g_err;

__device__ __forceinline__ uint32_t smem_u32(const void* p) { return (uint32_t)__cvta_generic_to_shared(p); }
__device__ __forceinline__ uint32_t mapa(uint32_t a, uint32_t r) {
  uint32_t o; asm("mapa.shared::cluster.u32 %0, %1, %2;" : "=r"(o) : "r"(a), "r"(r)); return o;
}
__device__ __forceinline__ void mbar_init(uint32_t bar, uint32_t cnt) {
  asm volatile("mbarrier.init.shared::cta.b64 [%0], %1;" ::"r"(bar), "r"(cnt) : "memory");
}
__device__ __forceinline__ void mbar_arrive(uint32_t bar) {
  asm volatile("mbarrier.arrive.shared::cta.b64 _, [%0];" ::"r"(bar) : "memory");
}
__device__ __forceinline__ void mbar_arrive_tx(uint32_t bar, uint32_t bytes) {
  asm volatile("mbarrier.arrive.expect_tx.shared::cta.b64 _, [%0], %1;" ::"r"(bar), "r"(bytes) : "memory");
}
__device__ __forceinline__ void mbar_arrive_remote(uint32_t cbar) {
  asm volatile("mbarrier.arrive.shared::cluster.b64 _, [%0];" ::"r"(cbar) : "memory");
}
__device__ __forceinline__ void mbar_arrive_remote_rel(uint32_t cbar) {
  asm volatile("mbarrier.arrive.release.cluster.shared::cluster.b64 _, [%0];" ::"r"(cbar) : "memory");
}
__device__ __forceinline__ bool mbar_try(uint32_t bar, uint32_t par) {
  uint32_t ok;
  asm volatile("{\n.reg .pred p;\nmbarrier.try_wait.parity.shared::cta.b64 p, [%1], %2;\nselp.u32 %0, 1, 0, p;\n}"
               : "=r"(ok) : "r"(bar), "r"(par) : "memory");
  return ok;
}
__device__ __forceinline__ bool mbar_try_acq(uint32_t bar, uint32_t par) {
  uint32_t ok;
  asm volatile("{\n.reg .pred p;\nmbarrier.try_wait.parity.acquire.cluster.shared::cta.b64 p, [%1], %2;\nselp.u32 %0, 1, 0, p;\n}"
               : "=r"(ok) : "r"(bar), "r"(par) : "memory");
  return ok;
}
__device__ __forceinline__ uint32_t clk32() { uint32_t c; asm volatile("mov.u32 %0, %%clock;" : "=r"(c)); return c; }
constexpr uint32_t WAIT_LIMIT = 1u << 26;
__device__ __forceinline__ void mbar_wait(uint32_t bar, uint32_t par) {
  if (mbar_try(bar, par)) return;
  const uint32_t t0 = clk32();
#pragma unroll 1
  for (uint32_t it = 1; !mbar_try(bar, par); it++) {
    if ((it & 63) == 0) {
      if (*(volatile unsigned int*)&g_err) return;
      if (clk32() - t0 > WAIT_LIMIT) { *(volatile unsigned int*)&g_err = 1; return; }
    }
  }
}
__device__ __forceinline__ void mbar_wait_acq(uint32_t bar, uint32_t par) {
  mbar_wait(bar, par);
  (void)mbar_try_acq(bar, par);
}
__device__ __forceinline__ void st_async32(uint32_t caddr, uint32_t v, uint32_t cbar) {
  asm volatile("st.async.weak.shared::cluster.mbarrier::complete_tx::bytes.b32 [%0], %1, [%2];" ::"r"(caddr), "r"(v), "r"(cbar) : "memory");
}
__device__ __forceinline__ void sts32(uint32_t a, uint32_t v) { asm volatile("st.shared.b32 [%0], %1;" ::"r"(a), "r"(v) : "memory"); }
__device__ __forceinline__ uint32_t lds32(uint32_t a) { uint32_t v; asm volatile("ld.shared.b32 %0, [%1];" : "=r"(v) : "r"(a) : "memory"); return v; }
__device__ __forceinline__ void sts128(uint32_t a, uint32_t x, uint32_t y, uint32_t z, uint32_t w) {
  asm volatile("st.shared.v4.b32 [%0], {%1,%2,%3,%4};" ::"r"(a), "r"(x), "r"(y), "r"(z), "r"(w) : "memory");
}
__device__ __forceinline__ void lds128(uint32_t a, uint32_t* r) {
  asm volatile("ld.shared.v4.b32 {%0,%1,%2,%3}, [%4];" : "=r"(r[0]), "=r"(r[1]), "=r"(r[2]), "=r"(r[3]) : "r"(a) : "memory");
}
__device__ __forceinline__ void ldsm4(uint32_t a, uint32_t* r) {
  asm volatile("ldmatrix.sync.aligned.m8n8.x4.shared.b16 {%0,%1,%2,%3}, [%4];" : "=r"(r[0]), "=r"(r[1]), "=r"(r[2]), "=r"(r[3]) : "r"(a) : "memory");
}
__device__ __forceinline__ void ldsm4t(uint32_t a, uint32_t* r) {
  asm volatile("ldmatrix.sync.aligned.m8n8.x4.trans.shared.b16 {%0,%1,%2,%3}, [%4];" : "=r"(r[0]), "=r"(r[1]), "=r"(r[2]), "=r"(r[3]) : "r"(a) : "memory");
}
__device__ __forceinline__ void ldsm2(uint32_t a, uint32_t* r) {
  asm volatile("ldmatrix.sync.aligned.m8n8.x2.shared.b16 {%0,%1}, [%2];" : "=r"(r[0]), "=r"(r[1]) : "r"(a) : "memory");
}
__device__ __forceinline__ void stsm4(uint32_t a, uint32_t r0, uint32_t r1, uint32_t r2, uint32_t r3) {
  asm volatile("stmatrix.sync.aligned.m8n8.x4.shared.b16 [%0], {%1,%2,%3,%4};" ::"r"(a), "r"(r0), "r"(r1), "r"(r2), "r"(r3) : "memory");
}
__device__ __forceinline__ void stsm4t(uint32_t a, uint32_t r0, uint32_t r1, uint32_t r2, uint32_t r3) {
  asm volatile("stmatrix.sync.aligned.m8n8.x4.trans.shared.b16 [%0], {%1,%2,%3,%4};" ::"r"(a), "r"(r0), "r"(r1), "r"(r2), "r"(r3) : "memory");
}
__device__ __forceinline__ void stsm2t(uint32_t a, uint32_t r0, uint32_t r1) {
  asm volatile("stmatrix.sync.aligned.m8n8.x2.trans.shared.b16 [%0], {%1,%2};" ::"r"(a), "r"(r0), "r"(r1) : "memory");
}
__device__ __forceinline__ void mma16816(float* c, const uint32_t* a, uint32_t b0, uint32_t b1) {
  asm volatile("mma.sync.aligned.m16n8k16.row.col.f32.bf16.bf16.f32 {%0,%1,%2,%3}, {%4,%5,%6,%7}, {%8,%9}, {%0,%1,%2,%3};"
               : "+f"(c[0]), "+f"(c[1]), "+f"(c[2]), "+f"(c[3]) : "r"(a[0]), "r"(a[1]), "r"(a[2]), "r"(a[3]), "r"(b0), "r"(b1));
}
__device__ __forceinline__ void mma16816r(float* c, uint32_t a0, uint32_t a1, uint32_t a2, uint32_t a3, uint32_t b0, uint32_t b1) {
  asm volatile("mma.sync.aligned.m16n8k16.row.col.f32.bf16.bf16.f32 {%0,%1,%2,%3}, {%4,%5,%6,%7}, {%8,%9}, {%0,%1,%2,%3};"
               : "+f"(c[0]), "+f"(c[1]), "+f"(c[2]), "+f"(c[3]) : "r"(a0), "r"(a1), "r"(a2), "r"(a3), "r"(b0), "r"(b1));
}
__device__ __forceinline__ void mma1688(float* c, uint32_t a0, uint32_t a1, uint32_t b0) {
  asm volatile("mma.sync.aligned.m16n8k8.row.col.f32.bf16.bf16.f32 {%0,%1,%2,%3}, {%4,%5}, {%6}, {%0,%1,%2,%3};"
               : "+f"(c[0]), "+f"(c[1]), "+f"(c[2]), "+f"(c[3]) : "r"(a0), "r"(a1), "r"(b0));
}
__device__ __forceinline__ uint32_t pack_bf16(float lo, float hi) {
  uint32_t r; asm("cvt.rn.bf16x2.f32 %0, %1, %2;" : "=r"(r) : "f"(hi), "f"(lo)); return r;
}
__device__ __forceinline__ float bf_lo(uint32_t w) { return __uint_as_float(w << 16); }
__device__ __forceinline__ float bf_hi(uint32_t w) { return __uint_as_float(w & 0xffff0000u); }
__device__ __forceinline__ float ex2(float x) { float y; asm("ex2.approx.ftz.f32 %0, %1;" : "=f"(y) : "f"(x)); return y; }
__device__ __forceinline__ float rcp(float x) { float y; asm("rcp.approx.ftz.f32 %0, %1;" : "=f"(y) : "f"(x)); return y; }
__device__ __forceinline__ void bar_sync(int id, int n) { asm volatile("bar.sync %0, %1;" ::"r"(id), "r"(n) : "memory"); }
__device__ __forceinline__ void bar_arrive(int id, int n) { asm volatile("bar.arrive %0, %1;" ::"r"(id), "r"(n) : "memory"); }
__device__ __forceinline__ void fence_async_smem() { asm volatile("fence.proxy.async.shared::cta;" ::: "memory"); }
__device__ __forceinline__ void fence_async_all() { asm volatile("fence.proxy.async;" ::: "memory"); }
__device__ __forceinline__ void cp_async16(uint32_t dst, const void* src) {
  asm volatile("cp.async.cg.shared.global [%0], [%1], 16;" ::"r"(dst), "l"(src) : "memory");
}
__device__ __forceinline__ void cp_async_wait_all() { asm volatile("cp.async.wait_all;" ::: "memory"); }
__device__ __forceinline__ void bulk_g2s(uint32_t dst, const void* src, uint32_t bytes, uint32_t bar) {
  asm volatile("cp.async.bulk.shared::cluster.global.mbarrier::complete_tx::bytes [%0], [%1], %2, [%3];"
               ::"r"(dst), "l"(src), "r"(bytes), "r"(bar) : "memory");
}
__device__ __forceinline__ void bulk_g2s_mc(uint32_t dst, const void* src, uint32_t bytes, uint32_t bar, uint16_t mask) {
  asm volatile("cp.async.bulk.shared::cluster.global.mbarrier::complete_tx::bytes.multicast::cluster [%0], [%1], %2, [%3], %4;"
               ::"r"(dst), "l"(src), "r"(bytes), "r"(bar), "h"(mask) : "memory");
}
__device__ __forceinline__ void bulk_s2g(void* dst, uint32_t src, uint32_t bytes) {
  asm volatile("cp.async.bulk.global.shared::cta.bulk_group [%0], [%1], %2;" ::"l"(dst), "r"(src), "r"(bytes) : "memory");
}
__device__ __forceinline__ void bulk_commit() { asm volatile("cp.async.bulk.commit_group;" ::: "memory"); }
__device__ __forceinline__ void bulk_wait_read() { asm volatile("cp.async.bulk.wait_group.read 0;" ::: "memory"); }
__device__ __forceinline__ void bulk_wait_all() { asm volatile("cp.async.bulk.wait_group 0;" ::: "memory"); }
__device__ __forceinline__ void tma2d(uint32_t dst, const CUtensorMap* m, int c0, int c1, uint32_t bar) {
  asm volatile("cp.async.bulk.tensor.2d.shared::cluster.global.mbarrier::complete_tx::bytes [%0], [%1, {%3, %4}], [%2];"
               ::"r"(dst), "l"(m), "r"(bar), "r"(c0), "r"(c1) : "memory");
}
__device__ __forceinline__ void pdl_wait() { asm volatile("griddepcontrol.wait;" ::: "memory"); }
__device__ __forceinline__ void pdl_launch() { asm volatile("griddepcontrol.launch_dependents;" ::: "memory"); }
__device__ __forceinline__ void cluster_sync() {
  asm volatile("barrier.cluster.arrive.aligned;\nbarrier.cluster.wait.aligned;" ::: "memory");
}
__device__ __forceinline__ uint64_t mkdesc(uint32_t saddr, uint32_t lbo, uint32_t sbo) {
  return (uint64_t)((saddr & 0x3FFFF) >> 4) | ((uint64_t)(lbo >> 4) << 16) | ((uint64_t)(sbo >> 4) << 32) | ((uint64_t)1 << 62);
}
__device__ __forceinline__ void wg_fence() { asm volatile("wgmma.fence.sync.aligned;" ::: "memory"); }
__device__ __forceinline__ void wg_commit() { asm volatile("wgmma.commit_group.sync.aligned;" ::: "memory"); }
template <int N> __device__ __forceinline__ void wg_wait() { asm volatile("wgmma.wait_group.sync.aligned %0;" ::"n"(N) : "memory"); }
__device__ __forceinline__ void wgmma_rs_n32(float* c, const uint32_t* a, uint64_t d, int acc) {
  asm volatile("{\n.reg .pred p;\nsetp.ne.b32 p, %21, 0;\n"
    "wgmma.mma_async.sync.aligned.m64n32k16.f32.bf16.bf16 {%0,%1,%2,%3,%4,%5,%6,%7,%8,%9,%10,%11,%12,%13,%14,%15}, {%16,%17,%18,%19}, %20, p, 1, 1, 0;\n}"
    : "+f"(c[0]), "+f"(c[1]), "+f"(c[2]), "+f"(c[3]), "+f"(c[4]), "+f"(c[5]), "+f"(c[6]), "+f"(c[7]),
      "+f"(c[8]), "+f"(c[9]), "+f"(c[10]), "+f"(c[11]), "+f"(c[12]), "+f"(c[13]), "+f"(c[14]), "+f"(c[15])
    : "r"(a[0]), "r"(a[1]), "r"(a[2]), "r"(a[3]), "l"(d), "r"(acc));
}
template <int R> __device__ __forceinline__ void reg_inc() { asm volatile("setmaxnreg.inc.sync.aligned.u32 %0;" ::"n"(R)); }
template <int R> __device__ __forceinline__ void reg_dec() { asm volatile("setmaxnreg.dec.sync.aligned.u32 %0;" ::"n"(R)); }

#define PROF_T(slot) do {} while (0)

__device__ __forceinline__ float bfr(float x) { return __bfloat162float(__float2bfloat16_rn(x)); }

__global__ void __launch_bounds__(256) k_ln(const __nv_bfloat16* __restrict__ x) {
  pdl_launch();
  const int tid = threadIdx.x, lane = tid & 31;
  const int gw = blockIdx.x * 8 + (tid >> 5);
  const int gt = blockIdx.x * 256 + tid;
  const uint4* src = reinterpret_cast<const uint4*>(x + (size_t)gw * DM);
  uint4 v0 = src[lane], v1 = src[lane + 32];
  {
    uint4 nanv = make_uint4(0xffffffffu, 0xffffffffu, 0xffffffffu, 0xffffffffu);
    uint4* ex = reinterpret_cast<uint4*>(g_ex);
    for (int i = gt; i < 4 * EX_BUF / 16; i += 65536) ex[i] = nanv;
    if (gt < NSEG) g_cnt[gt] = 0;
    if (gt < 16) g_hcnt[gt] = 0;
    if (gt == 0) g_err = 0;
  }
  float f[16];
  {
    uint32_t w[8] = {v0.x, v0.y, v0.z, v0.w, v1.x, v1.y, v1.z, v1.w};
#pragma unroll
    for (int i = 0; i < 8; i++) { f[2 * i] = bf_lo(w[i]); f[2 * i + 1] = bf_hi(w[i]); }
  }
  float sum = 0.f;
#pragma unroll
  for (int i = 0; i < 16; i++) sum += f[i];
#pragma unroll
  for (int o = 16; o; o >>= 1) sum += __shfl_xor_sync(0xffffffffu, sum, o);
  const float mean = sum * (1.f / DM);
  float sq = 0.f;
#pragma unroll
  for (int i = 0; i < 16; i++) { float d = f[i] - mean; sq += d * d; }
#pragma unroll
  for (int o = 16; o; o >>= 1) sq += __shfl_xor_sync(0xffffffffu, sq, o);
  const float mb = bfr(mean), vb = bfr(sq * (1.f / DM));
  const float sd = bfr(sqrtf(bfr(vb + 1e-5f)));
  uint32_t o[8];
#pragma unroll
  for (int i = 0; i < 8; i++) o[i] = pack_bf16(bfr(f[2 * i] - mb) / sd, bfr(f[2 * i + 1] - mb) / sd);
  {
    int c0 = lane, c1 = lane + 32;
    unsigned char* d0 = g_xn + ((size_t)(c0 >> 3) * S_TOK + gw) * 128 + (((c0 & 7) ^ (gw & 7)) << 4);
    unsigned char* d1 = g_xn + ((size_t)(c1 >> 3) * S_TOK + gw) * 128 + (((c1 & 7) ^ (gw & 7)) << 4);
    *reinterpret_cast<uint4*>(d0) = make_uint4(o[0], o[1], o[2], o[3]);
    *reinterpret_cast<uint4*>(d1) = make_uint4(o[4], o[5], o[6], o[7]);
  }
}

constexpr int SM_BAR = 0;
constexpr int SM_WO = 1024;
constexpr int SM_XN = SM_WO + 49152;
constexpr int SM_MEM = SM_XN + 32768;
constexpr int SM_STG = SM_MEM + 8192;
constexpr int SM_V = SM_STG;
constexpr int SM_VM = SM_V + NVST * 16384;
constexpr int SM_KX = SM_VM + 4 * 4096;
constexpr int SM_ATQ = SM_KX + 3 * 3072;
constexpr int SM_ATK = SM_ATQ + 8192;
constexpr int SM_KMA = SM_ATK + 8192;
constexpr int SM_SC = SM_KMA + 2 * 2048;
constexpr int SM_QS = SM_SC + 4096;
constexpr int SM_KS = SM_QS + 1024;
constexpr int SM_O = SM_KS + 1024;
constexpr int SM_STQ = SM_O + 4096;
constexpr int SM_STV = SM_STQ + 3072;
constexpr int SM_OX = SM_STV + 4096;
constexpr int SM_PAIR = SM_OX + 8192;
constexpr int SM_END = SM_PAIR + 1024;
static_assert(SM_STG + 131072 <= SM_END, "staging");
static_assert(SM_END <= 232448, "smem");
static_assert(SM_XN % 1024 == 0, "align");
constexpr int B_MEM = 0;
constexpr int B_SC = 3;
constexpr int B_VM = 4;
constexpr int B_XNF = 8;
constexpr int B_XNE = 9;
constexpr int B_VF = 10;
constexpr int B_VE = 14;
constexpr int B_STF = 18;
constexpr int B_STE = 19;
constexpr int B_ATF = 20;
constexpr int B_KMF = 21;
constexpr int B_QKR = 23;

constexpr float SC_LOG2E = 0.08838834764831845f * 1.4426950408889634f;

#define POLL_DELAY 250

__global__ void __launch_bounds__(512, 1)
k_chain(const __nv_bfloat16* __restrict__ mem0, const __nv_bfloat16* __restrict__ Wq, const __nv_bfloat16* __restrict__ Wk,
        const __nv_bfloat16* __restrict__ Wv, const __nv_bfloat16* __restrict__ Wo) {
  extern __shared__ __align__(1024) unsigned char smem[];
  const uint32_t sb = smem_u32(smem);
  const int tid = threadIdx.x, lane = tid & 31, warp = tid >> 5;
  uint32_t rank; asm("mov.u32 %0, %%cluster_ctarank;" : "=r"(rank));
  const int cl = blockIdx.x / CLS;
  const int hl = rank / 3, jj = rank - hl * 3;
  const int head = cl * 2 + hl;
  const int nqk = jj < 2 ? 3 : 2, nv = jj < 2 ? 2 : 4;
  const int qk0 = jj * 3, v0 = jj * 2;
  const int nu = rank < 2 ? 12 : 10;
  const int cb = rank < 2 ? rank * 12 : 24 + (rank - 2) * 10;
  auto BAR = [&](int i) { return sb + SM_BAR + 8 * i; };

  if (tid == 0) {
    mbar_init(BAR(B_MEM + 0), 4); mbar_init(BAR(B_MEM + 1), 4); mbar_init(BAR(B_MEM + 2), nu - 8);
    mbar_init(BAR(B_SC), 5);
    for (int i = 0; i < 4; i++) mbar_init(BAR(B_VM + i), nv);
    mbar_init(BAR(B_XNF), 1); mbar_init(BAR(B_XNE), 2 * CLS);
    for (int i = 0; i < NVST; i++) { mbar_init(BAR(B_VF + i), 1); mbar_init(BAR(B_VE + i), 4); }
    mbar_init(BAR(B_STF), 8); mbar_init(BAR(B_STE), 1);
    mbar_init(BAR(B_ATF), 1); mbar_init(BAR(B_KMF), 1); mbar_init(BAR(B_KMF + 1), 1);
    mbar_init(BAR(B_QKR), 3); mbar_init(BAR(B_QKR + 1), 3);
    asm volatile("fence.mbarrier_init.release.cluster;" ::: "memory");
  }
  if (warp < 8) {
    const __nv_bfloat16* W; int tile;
    if (warp < nqk) { W = Wq; tile = qk0 + warp; }
    else if (warp < 2 * nqk) { W = Wk; tile = qk0 + warp - nqk; }
    else { W = Wv; tile = v0 + warp - 2 * nqk; }
    const __nv_bfloat16* src = W + head * DH + tile * 16 + (lane & 1) * 8;
    const uint32_t dst = sb + SM_STG + warp * 16384;
#pragma unroll 8
    for (int i = 0; i < 32; i++) {
      int k = i * 16 + (lane >> 1);
      cp_async16(dst + k * 32 + (((lane & 1) ^ ((k >> 2) & 1)) << 4), src + (size_t)k * (NH * DH));
    }
  } else if (warp < 12) {
    const int a = warp - 8;
    const uint32_t dst = sb + SM_WO + a * 12288;
    const __nv_bfloat16* base = Wo + (size_t)cl * 256 * DM + cb * 8 + (lane & 1) * 8;
#pragma unroll 8
    for (int i = 0; i < 16; i++) {
      int kk = i * 16 + (lane >> 1);
      int k = (kk + 128 * (a & 1)) & 255;
      cp_async16(dst + 4096 + kk * 32 + (((lane & 1) ^ ((kk >> 2) & 1)) << 4), base + (size_t)k * DM + a * 16);
    }
    if (4 + (a >> 1) < nu / 2) {
#pragma unroll 8
      for (int i = 0; i < 8; i++) {
        int kk = i * 16 + (lane >> 1);
        int k = kk + 128 * (a & 1);
        cp_async16(dst + kk * 32 + (((lane & 1) ^ ((kk >> 2) & 1)) << 4), base + (size_t)k * DM + (4 + (a >> 1)) * 16);
      }
    }
  }
  __syncthreads();
  cluster_sync();

  if (warp < 8) {
    reg_inc<176>();
    uint32_t W[32][4];
    {
      cp_async_wait_all();
      __syncwarp();
      const int kr = (lane & 7) + ((lane >> 4) << 3), ch = (lane >> 3) & 1;
      const uint32_t a0 = sb + SM_STG + warp * 16384 + kr * 32 + ((ch ^ ((kr >> 2) & 1)) << 4);
#pragma unroll
      for (int ks = 0; ks < 32; ks++) ldsm4t(a0 + ks * 512, W[ks]);
    }
    cluster_sync();
    const int role = warp < nqk ? 0 : (warp < 2 * nqk ? 1 : 2);
    const int tl = role == 0 ? warp : (role == 1 ? warp - nqk : warp - 2 * nqk);
    const int wg = warp >> 2;
    const int nqkbar = jj < 2 ? 192 : 160;

    auto bulk = [&](int g) {
      float c[16];
      mbar_wait(BAR(B_XNF), g & 1);
      uint32_t dlo = (((sb + SM_XN) & 0x3FFFF) >> 4) | (1u << 16);
      asm volatile("" : "+r"(dlo));
      wg_fence();
#pragma unroll
      for (int ks = 0; ks < 32; ks++)
        wgmma_rs_n32(c, W[ks], ((uint64_t)0x40000040u << 32) | (uint64_t)(dlo + (ks >> 2) * 256 + (ks & 3) * 2), ks);
      wg_commit();
      wg_wait<0>();
      if ((tid & 127) == 0) mbar_arrive_remote(mapa(BAR(B_XNE), 0));
      if (g > 0) mbar_wait(BAR(B_STE), (g - 1) & 1);
      uint32_t r[8];
#pragma unroll
      for (int nt = 0; nt < 4; nt++) { r[nt] = pack_bf16(c[4 * nt], c[4 * nt + 1]); r[4 + nt] = pack_bf16(c[4 * nt + 2], c[4 * nt + 3]); }
      if (role == 2) {
        uint32_t d = sb + SM_STV + tl * 1024 + lane * 16;
        stsm4(d, r[0], r[1], r[2], r[3]); stsm4(d + 512, r[4], r[5], r[6], r[7]);
      } else {
        uint32_t d = sb + (role == 0 ? SM_STQ : SM_KX + (g % 3) * 3072) + tl * 1024 + lane * 16;
        stsm4t(d, r[0], r[1], r[2], r[3]); stsm4t(d + 512, r[4], r[5], r[6], r[7]);
      }
      fence_async_smem();
      __syncwarp();
      if (lane == 0) mbar_arrive(BAR(B_STF));
    };

#pragma unroll 1
    for (int s = -2; s < NSEG; s++) {
     if (s >= 0) {
      if (s == 0) bar_sync(1, 256);
      uint32_t kb[6];
      if (warp < 4) {
        const uint32_t a = sb + SM_KX + (s % 3) * 3072 + warp * 128 + (lane >> 3) * 512 + (lane & 7) * 16;
        ldsm4(a, kb);
        if (nqk == 3) ldsm2(a + 2048, kb + 4);
      }
      if (role == 2) mbar_wait(BAR(B_VF + (s % NVST)), (s / NVST) & 1);
      float acc[4][4];
#pragma unroll
      for (int i = 0; i < 4; i++) { acc[i][0] = acc[i][1] = acc[i][2] = acc[i][3] = 0.f; }
      const uint32_t ma = sb + SM_MEM + lane * 16;
      const uint32_t par = s & 1;
#define KPAIR(ks, i) { uint32_t b[4]; ldsm4t(ma + (ks) * 256, b); mma16816(acc[(i)], W[(ks)], b[0], b[1]); mma16816(acc[(i) + 1], W[(ks) + 1], b[2], b[3]); }
      mbar_wait(BAR(B_MEM + 0), par);
      if (warp == 0) PROF_T(0);
      KPAIR(0, 0) KPAIR(6, 2) KPAIR(12, 0) KPAIR(17, 2) KPAIR(22, 0) KPAIR(27, 2)
      mbar_wait(BAR(B_MEM + 1), par);
      KPAIR(2, 0) KPAIR(8, 2) KPAIR(14, 0) KPAIR(19, 2) KPAIR(24, 0) KPAIR(29, 2)
      mbar_wait(BAR(B_MEM + 2), par);
      if (warp == 0) PROF_T(1);
      KPAIR(4, 0) KPAIR(10, 2)
      {
        uint32_t b[4];
        ldsm4t(sb + SM_MEM + (lane < 16 ? 16 : 21) * 256 + (lane & 15) * 16, b);
        mma16816(acc[0], W[16], b[0], b[1]); mma16816(acc[1], W[21], b[2], b[3]);
        ldsm4t(sb + SM_MEM + (lane < 16 ? 26 : 31) * 256 + (lane & 15) * 16, b);
        mma16816(acc[2], W[26], b[0], b[1]); mma16816(acc[3], W[31], b[2], b[3]);
      }
#undef KPAIR
      const uint32_t w0 = pack_bf16((acc[0][0] + acc[1][0]) + (acc[2][0] + acc[3][0]), (acc[0][1] + acc[1][1]) + (acc[2][1] + acc[3][1]));
      const uint32_t w1 = pack_bf16((acc[0][2] + acc[1][2]) + (acc[2][2] + acc[3][2]), (acc[0][3] + acc[1][3]) + (acc[2][3] + acc[3][3]));
      if (role < 2) {
        stsm2t(sb + (role == 0 ? SM_QS : SM_KS) + tl * 256 + (lane & 15) * 16, w0, w1);
      } else {
        const uint32_t off = SM_VM + (s & 3) * 4096 + (hl * 16 + (v0 + tl) * 2) * 128 + lane * 4;
        const uint32_t vb = BAR(B_VM + (s & 3));
#pragma unroll
        for (int d = 1; d < CLS; d++) {
          uint32_t t = rank + d; if (t >= CLS) t -= CLS;
          const uint32_t ra = mapa(sb + off, t), rb = mapa(vb, t);
          st_async32(ra, w0, rb); st_async32(ra + 128, w1, rb);
        }
        sts32(sb + off, w0); sts32(sb + off + 128, w1);
        __syncwarp();
        if (lane == 0) { if (tl == 0) mbar_arrive_tx(vb, 4096 - nv * 256); else mbar_arrive(vb); }
      }
      if (warp < 5) bar_sync(2, nqkbar); else if (warp == 5 && jj < 2) bar_arrive(2, nqkbar);
      if (warp == 0) PROF_T(2);
      if (s < NSEG - 1) {
        if (warp < 5) {
          uint32_t qa[6];
          ldsm4(sb + SM_QS + lane * 16, qa);
          if (warp == 4) ldsm4(sb + SM_KS + lane * 16, kb);
          float c[4] = {0.f, 0.f, 0.f, 0.f}, c2[4] = {0.f, 0.f, 0.f, 0.f};
          if (nqk == 3) {
            ldsm2(sb + SM_QS + 512 + (lane & 15) * 16, qa + 4);
            if (warp == 4) ldsm2(sb + SM_KS + 512 + (lane & 15) * 16, kb + 4);
          }
          mma16816r(c, qa[0], 0u, qa[1], 0u, kb[0], kb[1]);
          mma16816r(c2, qa[2], 0u, qa[3], 0u, kb[2], kb[3]);
          if (nqk == 3) mma16816r(c, qa[4], 0u, qa[5], 0u, kb[4], kb[5]);
          const uint32_t wv = pack_bf16(c[0] + c2[0], c[1] + c2[1]);
          const uint32_t off = SM_SC + rank * 640 + warp * 128 + lane * 4;
#pragma unroll
          for (int d = 1; d < CLS; d++) {
            uint32_t t = rank + d; if (t >= CLS) t -= CLS;
            st_async32(mapa(sb + off, t), wv, mapa(BAR(B_SC), t));
          }
          sts32(sb + off, wv);
          __syncwarp();
          if (lane == 0) { if (warp == 0) mbar_arrive_tx(BAR(B_SC), 5 * 640); else mbar_arrive(BAR(B_SC)); }
        }
      }
      if (role == 1) {
        __syncwarp();
        const uint32_t own = hl * 3 + (s % 3);
        const uint32_t x0 = lds32(sb + SM_KS + tl * 256 + lane * 4), x1 = lds32(sb + SM_KS + tl * 256 + 128 + lane * 4);
        const uint32_t kp = (s / 3) & 1;
        const uint32_t ra = mapa(sb + SM_KMA + kp * 2048 + (qk0 + tl) * 256 + lane * 4, own), rb = mapa(BAR(B_KMF + kp), own);
        st_async32(ra, x0, rb); st_async32(ra + 128, x1, rb);
      }
      if (s < NSEG - 1) {
        if (warp == 0) PROF_T(3);
        uint32_t va[4][4];
        mbar_wait(BAR(B_VF + (s % NVST)), (s / NVST) & 1);
        {
          const uint32_t a = sb + SM_V + (s % NVST) * 16384 + (4 * warp + ((lane >> 3) & 1)) * 512 + (lane >> 4) * 128 + (lane & 7) * 16;
          ldsm4(a, va[0]); ldsm4(a + 256, va[1]); ldsm4(a + 1024, va[2]); ldsm4(a + 1280, va[3]);
        }
        mbar_wait(BAR(B_SC), par);
        if (warp == 0) PROF_T(4);
        float sv[10];
        {
          const uint32_t a = sb + SM_SC + (warp >> 2) * 1920;
          uint32_t r0[4], r1[4], r2[4], r3[4];
          ldsm4(a + lane * 16, r0); ldsm4(a + 640 + lane * 16, r1); ldsm4(a + 1280 + lane * 16, r2);
          ldsm4(a + min(lane >> 3, 2) * 640 + 512 + (lane & 7) * 16, r3);
#pragma unroll
          for (int g = 0; g < 4; g++) {
            sv[2 * g] = bf_lo(r0[g]) + bf_lo(r1[g]) + bf_lo(r2[g]);
            sv[2 * g + 1] = bf_hi(r0[g]) + bf_hi(r1[g]) + bf_hi(r2[g]);
          }
          sv[8] = bf_lo(r3[0]) + bf_lo(r3[1]) + bf_lo(r3[2]);
          sv[9] = bf_hi(r3[0]) + bf_hi(r3[1]) + bf_hi(r3[2]);
        }
        float mx = fmaxf(fmaxf(fmaxf(sv[0], sv[1]), fmaxf(sv[2], sv[3])), fmaxf(fmaxf(sv[4], sv[5]), fmaxf(sv[6], sv[7])));
        mx = fmaxf(mx, fmaxf(sv[8], sv[9]));
        mx = fmaxf(mx, __shfl_xor_sync(0xffffffffu, mx, 1));
        mx = fmaxf(mx, __shfl_xor_sync(0xffffffffu, mx, 2));
        const float nm = -mx * SC_LOG2E;
        uint32_t pb[5];
#pragma unroll
        for (int g = 0; g < 5; g++) pb[g] = pack_bf16(ex2(fmaf(sv[2 * g], SC_LOG2E, nm)), ex2(fmaf(sv[2 * g + 1], SC_LOG2E, nm)));
        float o0[4] = {0.f, 0.f, 0.f, 0.f}, o1[4] = {0.f, 0.f, 0.f, 0.f}, sm[4] = {0.f, 0.f, 0.f, 0.f};
        const uint32_t one = 0x3f803f80u;
        mma16816r(sm, one, one, one, one, pb[0], pb[1]);
        mma16816(o0, va[0], pb[0], pb[1]);
        mma16816(o1, va[2], pb[0], pb[1]);
        mma16816r(sm, one, one, one, one, pb[2], pb[3]);
        mma16816(o0, va[1], pb[2], pb[3]);
        mma16816(o1, va[3], pb[2], pb[3]);
        mma1688(sm, one, one, pb[4]);
        uint32_t vm[4];
        mbar_wait(BAR(B_VM + (s & 3)), (s >> 2) & 1);
        ldsm4(sb + SM_VM + (s & 3) * 4096 + warp * 512 + lane * 16, vm);
        mma1688(o0, vm[0], vm[1], pb[4]);
        mma1688(o1, vm[2], vm[3], pb[4]);
        const float i0 = rcp(sm[0]), i1 = rcp(sm[1]);
        const uint32_t oa = sb + SM_O + warp * 512 + lane * 4;
        sts32(oa, pack_bf16(o0[0] * i0, o0[1] * i1));
        sts32(oa + 128, pack_bf16(o0[2] * i0, o0[3] * i1));
        sts32(oa + 256, pack_bf16(o1[0] * i0, o1[1] * i1));
        sts32(oa + 384, pack_bf16(o1[2] * i0, o1[3] * i1));
        bar_arrive(3, 384);
        if (warp == 0) PROF_T(5);
      }
     }
      if (s + 2 < NSEG) bulk(s + 2);
      if (warp == 0 && s >= 0) PROF_T(6);
    }
    (void)wg;
    mbar_wait(BAR(B_VF + ((NSEG - 1) % NVST)), ((NSEG - 1) / NVST) & 1);
    mbar_wait(BAR(B_VM + ((NSEG - 1) & 3)), ((NSEG - 1) >> 2) & 1);
    cluster_sync();
  } else if (warp < 12) {
    reg_dec<104>();
    const int a = warp - 8;
    const bool has_half = 4 + (a >> 1) < nu / 2;
    const uint32_t wo = sb + SM_WO + a * 12288;
    {
      uint32_t F[24][4];
      cp_async_wait_all();
      __syncwarp();
      const int kr = (lane & 7) + ((lane >> 4) << 3), ch = (lane >> 3) & 1;
      const uint32_t a0 = wo + kr * 32 + ((ch ^ ((kr >> 2) & 1)) << 4);
#pragma unroll
      for (int u = 0; u < 24; u++) ldsm4t(a0 + u * 512, F[u]);
      __syncwarp();
#pragma unroll
      for (int u = 0; u < 24; u++) sts128(wo + u * 512 + lane * 16, F[u][0], F[u][1], F[u][2], F[u][3]);
      __syncwarp();
    }
    cluster_sync();
    pdl_wait();
    if (tid == 256) pdl_launch();

    uint32_t rmem[CLS - 1], rbar[CLS - 1];
#pragma unroll
    for (int d = 1; d < CLS; d++) {
      uint32_t t = rank + d; if (t >= CLS) t -= CLS;
      rmem[d - 1] = mapa(sb + SM_MEM + (cb + a) * 128 + lane * 4, t);
      rbar[d - 1] = mapa(BAR(B_MEM), t);
    }
    auto send_unit = [&](int wv, uint32_t val) {
#pragma unroll
      for (int d = 0; d < CLS - 1; d++) st_async32(rmem[d] + wv * 512, val, rbar[d] + wv * 8);
      sts32(sb + SM_MEM + (cb + a + 4 * wv) * 128 + lane * 4, val);
      __syncwarp();
      if (lane == 0) {
        if (a == 0) mbar_arrive_tx(BAR(B_MEM + wv), wv < 2 ? 5 * 512 : (16 - (nu - 8)) * 128);
        else mbar_arrive(BAR(B_MEM + wv));
      }
    };
    const bool has3 = a + 8 < nu;
    {
      const unsigned short* m0 = reinterpret_cast<const unsigned short*>(mem0);
#pragma unroll
      for (int wv = 0; wv < 3; wv++) {
        if (wv < 2 || has3) {
          const int col = (cb + a + 4 * wv) * 8 + (lane >> 2), r = (lane & 3) * 2;
          uint32_t val = (uint32_t)m0[r * DM + col] | ((uint32_t)m0[(r + 1) * DM + col] << 16);
          send_unit(wv, val);
        }
      }
    }
    const uint32_t n8 = lane >> 2;
    unsigned char* exw = g_ex + rank * EX_RANK + cl * 128 + lane * 4;
    const unsigned char* exr = g_ex + rank * EX_RANK + a * 2048 + (lane & 3) * 128 + (lane >> 2) * 16;

    for (int s = 0; s < NSEG - 1; s++) {
      uint32_t F[24][4];
      mbar_wait(BAR(B_MEM + 2), s & 1);
      {
        uint32_t t0 = clk32();
        while (clk32() - t0 < 200) {}
      }
#pragma unroll
      for (int u = 0; u < 16; u++) {
        if (u >= 8 || has_half) lds128(wo + u * 512 + lane * 16, F[u]);
        else F[u][0] = F[u][1] = F[u][2] = F[u][3] = 0u;
      }
      bar_sync(3, 384);
      if (a == 0) PROF_T(8);
      float hf[4] = {0.f, 0.f, 0.f, 0.f}, hg[4] = {0.f, 0.f, 0.f, 0.f}, f0[4] = {0.f, 0.f, 0.f, 0.f}, f1[4] = {0.f, 0.f, 0.f, 0.f};
      const uint32_t oa = sb + SM_O + lane * 16;
#pragma unroll
      for (int i = 0; i < 8; i++) {
        uint32_t b[4];
        ldsm4t(oa + ((i + 4 * (a & 1)) & 7) * 512, b);
        if (i < 4 && has_half) { mma16816(hf, F[2 * i], b[0], b[1]); mma16816(hg, F[2 * i + 1], b[2], b[3]); }
        mma16816(f0, F[8 + 2 * i], b[0], b[1]);
        mma16816(f1, F[8 + 2 * i + 1], b[2], b[3]);
        if (i < 4) { lds128(wo + (16 + 2 * i) * 512 + lane * 16, F[16 + 2 * i]); lds128(wo + (17 + 2 * i) * 512 + lane * 16, F[17 + 2 * i]); }
        if (i == 4 && has_half && (a & 1)) {
          sts128(sb + SM_PAIR + (a >> 1) * 512 + lane * 16, __float_as_uint(hf[0] + hg[0]), __float_as_uint(hf[1] + hg[1]),
                 __float_as_uint(hf[2] + hg[2]), __float_as_uint(hf[3] + hg[3]));
          bar_arrive(4 + (a >> 1), 64);
        }
      }
      unsigned char* wp = exw + (s & 3) * EX_BUF;
      if (has_half && !(a & 1)) {
        bar_sync(4 + (a >> 1), 64);
        uint32_t p[4];
        lds128(sb + SM_PAIR + (a >> 1) * 512 + lane * 16, p);
        const uint32_t x0 = pack_bf16(hf[0] + hg[0] + __uint_as_float(p[0]), hf[1] + hg[1] + __uint_as_float(p[1]));
        const uint32_t x1 = pack_bf16(hf[2] + hg[2] + __uint_as_float(p[2]), hf[3] + hg[3] + __uint_as_float(p[3]));
        asm volatile("st.relaxed.gpu.global.b32 [%0], %1;" ::"l"(wp + (8 + a) * 2048), "r"(x0) : "memory");
        asm volatile("st.relaxed.gpu.global.b32 [%0], %1;" ::"l"(wp + (9 + a) * 2048), "r"(x1) : "memory");
      }
      {
        const uint32_t x0 = pack_bf16(f0[0] + f1[0], f0[1] + f1[1]), x1 = pack_bf16(f0[2] + f1[2], f0[3] + f1[3]);
        asm volatile("st.relaxed.gpu.global.b32 [%0], %1;" ::"l"(wp + (2 * a) * 2048), "r"(x0) : "memory");
        asm volatile("st.relaxed.gpu.global.b32 [%0], %1;" ::"l"(wp + (2 * a + 1) * 2048), "r"(x1) : "memory");
      }
      if (a == 0) PROF_T(9);
      const uint32_t tw = clk32();
      {
        unsigned char* rp = exw + ((s + 2) & 3) * EX_BUF;
        asm volatile("st.relaxed.gpu.global.b32 [%0], %1;" ::"l"(rp + a * 2048), "r"(0xffffffffu) : "memory");
        asm volatile("st.relaxed.gpu.global.b32 [%0], %1;" ::"l"(rp + (a + 4) * 2048), "r"(0xffffffffu) : "memory");
        asm volatile("st.relaxed.gpu.global.b32 [%0], %1;" ::"l"(rp + (a + 8) * 2048), "r"(0xffffffffu) : "memory");
      }
      while (clk32() - tw < POLL_DELAY) {}
      const unsigned char* rp = exr + (s & 3) * EX_BUF;
      uint32_t pend = has3 ? 7u : 3u;
      int it = 0;
      while (true) {
        uint32_t v[3][4][4];
#pragma unroll
        for (int wv = 0; wv < 3; wv++) {
          if (pend & (1u << wv)) {
#pragma unroll
            for (int i = 0; i < 4; i++)
              asm volatile("ld.relaxed.gpu.global.v4.b32 {%0,%1,%2,%3}, [%4];"
                           : "=r"(v[wv][i][0]), "=r"(v[wv][i][1]), "=r"(v[wv][i][2]), "=r"(v[wv][i][3])
                           : "l"(rp + wv * 8192 + i * 512) : "memory");
          } else {
#pragma unroll
            for (int i = 0; i < 4; i++) v[wv][i][0] = v[wv][i][1] = v[wv][i][2] = v[wv][i][3] = 0u;
          }
        }
#pragma unroll
        for (int wv = 0; wv < 3; wv++) {
          if (pend & (1u << wv)) {
            float c0[4] = {0.f, 0.f, 0.f, 0.f}, c1[4] = {0.f, 0.f, 0.f, 0.f};
#pragma unroll
            for (int j = 0; j < 4; j++) {
              const uint32_t sel = (n8 == 2 * j ? 0x3f80u : 0u) | (n8 == 2 * j + 1 ? 0x3f800000u : 0u);
              mma16816r((j & 1) ? c1 : c0, v[wv][0][j], v[wv][1][j], v[wv][2][j], v[wv][3][j], sel, sel);
            }
            const float r0 = (c0[0] + c0[2]) + (c1[0] + c1[2]), r1 = (c0[1] + c0[3]) + (c1[1] + c1[3]);
            const bool bad = (r0 != r0) || (r1 != r1);
            if (!__any_sync(0xffffffffu, bad) || it > 20000) {
              send_unit(wv, pack_bf16(r0, r1));
              pend &= ~(1u << wv);
            }
          }
        }
        if (!pend) break;
        it++;
        if ((it & 255) == 0 && *(volatile unsigned int*)&g_err) it = 1 << 20;
      }
      if (it > 20000) *(volatile unsigned int*)&g_err = 2;
      if (a == 0) PROF_T(10);
    }
    __syncwarp();
    cluster_sync();
  } else {
    reg_dec<56>();
    if (warp == 15) {
      pdl_wait();
      if (lane == 0) {
        mbar_arrive_tx(BAR(B_XNF), 32768);
        if (rank == 0) {
#pragma unroll 1
          for (int kc = 0; kc < 8; kc++)
            bulk_g2s_mc(sb + SM_XN + kc * 4096, g_xn + (size_t)kc * S_TOK * 128, 4096, BAR(B_XNF), 0x3f);
        }
      }
      __syncwarp();
      cluster_sync();
      if (lane == 0) {
        for (int g = 1; g < NSEG; g++) {
          mbar_wait(BAR(B_STF), (g - 1) & 1);
          mbar_arrive_tx(BAR(B_XNF), 32768);
          if (rank == 0) {
            mbar_wait(BAR(B_XNE), (g - 1) & 1);
            if (g >= 3) {
              const uint32_t t0 = clk32();
              while (!mbar_try(BAR(B_MEM + 2), (g - 2) & 1) && clk32() - t0 < 1500) {}
            }
#pragma unroll 1
            for (int kc = 0; kc < 8; kc++)
              bulk_g2s_mc(sb + SM_XN + kc * 4096, g_xn + ((size_t)kc * S_TOK + g * 32) * 128, 4096, BAR(B_XNF), 0x3f);
          }
        }
      }
    } else if (warp == 12) {
      cluster_sync();
      if (lane == 0) {
        for (int g = 0; g < NSEG; g++) {
          const int slot = g & 3, slot8 = g & 7;
          mbar_arrive_tx(BAR(B_VF + (g % NVST)), 16384);
          mbar_wait(BAR(B_STF), g & 1);
          unsigned char* vdst = g_v + (size_t)(slot * NCL + cl) * 16384 + (hl * 16 + v0 * 2) * 512;
          bulk_s2g(vdst, sb + SM_STV, nv * 1024);
          bulk_s2g(g_q + (size_t)(slot8 * NH + head) * 8192 + qk0 * 1024, sb + SM_STQ, nqk * 1024);
          bulk_s2g(g_k + (size_t)(slot8 * NH + head) * 8192 + qk0 * 1024, sb + SM_KX + (g % 3) * 3072, nqk * 1024);
          bulk_commit();
          bulk_wait_read();
          mbar_arrive(BAR(B_STE));
          bulk_wait_all();
          fence_async_all();
          mbar_arrive_remote_rel(mapa(BAR(B_QKR + ((g / 3) & 1)), hl * 3 + (g % 3)));
          if (g >= NVST) mbar_wait(BAR(B_VE + (g % NVST)), ((g / NVST) - 1) & 1);
          bulk_g2s_mc(sb + SM_V + (g % NVST) * 16384 + (hl * 16 + v0 * 2) * 512, vdst, nv * 1024, BAR(B_VF + (g % NVST)), 0x3f);
        }
      }
    } else {
      cluster_sync();
      pdl_wait();
      const int rt = warp - 13;
      int n = 0;
      if (rt == 0 && lane == 0) mbar_arrive_tx(BAR(B_KMF), 2048);
      for (int g = jj; g < NSEG; g += 3, n++) {
        if (rt == 0 && lane == 0) {
          if (g + 3 < NSEG) mbar_arrive_tx(BAR(B_KMF + ((n + 1) & 1)), 2048);
          mbar_wait_acq(BAR(B_QKR + (n & 1)), (n >> 1) & 1);
          fence_async_all();
          mbar_arrive_tx(BAR(B_ATF), 16384);
          bulk_g2s(sb + SM_ATQ, g_q + (size_t)((g & 7) * NH + head) * 8192, 8192, BAR(B_ATF));
          bulk_g2s(sb + SM_ATK, g_k + (size_t)((g & 7) * NH + head) * 8192, 8192, BAR(B_ATF));
        }
        __syncwarp();
        mbar_wait(BAR(B_ATF), n & 1);
        mbar_wait(BAR(B_KMF + (n & 1)), (n >> 1) & 1);
        float sc[5][4];
#pragma unroll
        for (int t = 0; t < 5; t++) sc[t][0] = sc[t][1] = sc[t][2] = sc[t][3] = 0.f;
        {
          const uint32_t qa = sb + SM_ATQ + (lane >> 4) * 512 + (2 * rt + ((lane >> 3) & 1)) * 128 + (lane & 7) * 16;
          const uint32_t ka = sb + SM_ATK + lane * 16;
          const uint32_t kma = sb + SM_KMA + (n & 1) * 2048 + (lane & 15) * 16;
#pragma unroll 2
          for (int ks = 0; ks < 8; ks++) {
            uint32_t q[4], b0[4], b1[4], bm[2];
            ldsm4(qa + ks * 1024, q);
            ldsm4(ka + ks * 1024, b0); ldsm4(ka + ks * 1024 + 512, b1);
            ldsm2(kma + ks * 256, bm);
            mma16816(sc[0], q, b0[0], b1[0]);
            mma16816(sc[1], q, b0[1], b1[1]);
            if (rt) { mma16816(sc[2], q, b0[2], b1[2]); mma16816(sc[3], q, b0[3], b1[3]); }
            mma16816(sc[4], q, bm[0], bm[1]);
          }
        }
        const int r0 = 16 * rt + (lane >> 2), kq = (lane & 3) * 2;
        float m0 = fmaxf(sc[4][0], sc[4][1]), m1 = fmaxf(sc[4][2], sc[4][3]);
#pragma unroll
        for (int t = 0; t < 4; t++) {
          const int k0 = 8 * t + kq;
          if (k0 > r0) sc[t][0] = -INFINITY;
          if (k0 + 1 > r0) sc[t][1] = -INFINITY;
          if (k0 > r0 + 8) sc[t][2] = -INFINITY;
          if (k0 + 1 > r0 + 8) sc[t][3] = -INFINITY;
          m0 = fmaxf(m0, fmaxf(sc[t][0], sc[t][1]));
          m1 = fmaxf(m1, fmaxf(sc[t][2], sc[t][3]));
        }
        m0 = fmaxf(m0, __shfl_xor_sync(0xffffffffu, m0, 1)); m0 = fmaxf(m0, __shfl_xor_sync(0xffffffffu, m0, 2));
        m1 = fmaxf(m1, __shfl_xor_sync(0xffffffffu, m1, 1)); m1 = fmaxf(m1, __shfl_xor_sync(0xffffffffu, m1, 2));
        const float n0 = -m0 * SC_LOG2E, n1 = -m1 * SC_LOG2E;
        uint32_t p[5][2];
        float l0 = 0.f, l1 = 0.f;
#pragma unroll
        for (int t = 0; t < 5; t++) {
          p[t][0] = pack_bf16(ex2(fmaf(sc[t][0], SC_LOG2E, n0)), ex2(fmaf(sc[t][1], SC_LOG2E, n0)));
          p[t][1] = pack_bf16(ex2(fmaf(sc[t][2], SC_LOG2E, n1)), ex2(fmaf(sc[t][3], SC_LOG2E, n1)));
          l0 += bf_lo(p[t][0]) + bf_hi(p[t][0]);
          l1 += bf_lo(p[t][1]) + bf_hi(p[t][1]);
        }
        l0 += __shfl_xor_sync(0xffffffffu, l0, 1); l0 += __shfl_xor_sync(0xffffffffu, l0, 2);
        l1 += __shfl_xor_sync(0xffffffffu, l1, 1); l1 += __shfl_xor_sync(0xffffffffu, l1, 2);
        const float i0 = 1.f / l0, i1 = 1.f / l1;
        mbar_wait(BAR(B_VF + (g % NVST)), (g / NVST) & 1);
        mbar_wait(BAR(B_VM + (g & 3)), (g >> 2) & 1);
        if (n > 0) { if (lane == 0) bulk_wait_read(); __syncwarp(); }
        {
          const uint32_t va = sb + SM_V + (g % NVST) * 16384 + hl * 8192 + lane * 16;
          const uint32_t vma = sb + SM_VM + (g & 3) * 4096 + hl * 2048 + (lane & 15) * 16;
          const int row = (lane & 7) + ((lane >> 3) & 1) * 8;
          const uint32_t oxb = sb + SM_OX + rt * 4096 + row * 128;
#pragma unroll 2
          for (int np = 0; np < 8; np++) {
            uint32_t x0[4], x1[4], xm[2];
            ldsm4(va + np * 1024, x0); ldsm4(va + np * 1024 + 512, x1);
            ldsm2(vma + np * 256, xm);
            float o0[4] = {0.f, 0.f, 0.f, 0.f}, o1[4] = {0.f, 0.f, 0.f, 0.f};
            mma16816r(o0, p[0][0], p[0][1], p[1][0], p[1][1], x0[0], x0[1]);
            mma16816r(o1, p[0][0], p[0][1], p[1][0], p[1][1], x1[0], x1[1]);
            if (rt) {
              mma16816r(o0, p[2][0], p[2][1], p[3][0], p[3][1], x0[2], x0[3]);
              mma16816r(o1, p[2][0], p[2][1], p[3][0], p[3][1], x1[2], x1[3]);
            }
            mma1688(o0, p[4][0], p[4][1], xm[0]);
            mma1688(o1, p[4][0], p[4][1], xm[1]);
            const int c16 = (2 * np + (lane >> 4));
            stsm4(oxb + (c16 >> 3) * 2048 + (((c16 & 7) ^ (row & 7)) << 4),
                  pack_bf16(o0[0] * i0, o0[1] * i0), pack_bf16(o0[2] * i1, o0[3] * i1),
                  pack_bf16(o1[0] * i0, o1[1] * i0), pack_bf16(o1[2] * i1, o1[3] * i1));
          }
        }
        fence_async_smem();
        __syncwarp();
        if (lane < CLS) mbar_arrive_remote(mapa(BAR(B_VE + (g % NVST)), lane));
        if (lane == 0) {
          unsigned char* dst = g_ox + ((size_t)(head * 2) * S_TOK + g * 32 + rt * 16) * 128;
          bulk_s2g(dst, sb + SM_OX + rt * 4096, 2048);
          bulk_s2g(dst + (size_t)S_TOK * 128, sb + SM_OX + rt * 4096 + 2048, 2048);
          bulk_commit();
          bulk_wait_all();
          fence_async_all();
          asm volatile("red.release.gpu.global.add.u32 [%0], 1;" ::"l"(&g_cnt[g]) : "memory");
        }
        bar_sync(6, 64);
      }
    }
    __syncwarp();
    cluster_sync();
  }
}

constexpr int G_STAGES = 4, G_STAGE_BYTES = 49152;
constexpr int G_SM_BAR = G_STAGES * G_STAGE_BYTES;
constexpr int G_SM_END = G_SM_BAR + 1024 + 32768;
__device__ __forceinline__ void wgmma_ss_n256(float* c, uint64_t da, uint64_t db, int acc) {
  asm volatile("{\n.reg .pred p;\nsetp.ne.b32 p, %130, 0;\n"
    "wgmma.mma_async.sync.aligned.m64n256k16.f32.bf16.bf16 {"
    "%0,%1,%2,%3,%4,%5,%6,%7,%8,%9,%10,%11,%12,%13,%14,%15,%16,%17,%18,%19,%20,%21,%22,%23,%24,%25,%26,%27,%28,%29,%30,%31,"
    "%32,%33,%34,%35,%36,%37,%38,%39,%40,%41,%42,%43,%44,%45,%46,%47,%48,%49,%50,%51,%52,%53,%54,%55,%56,%57,%58,%59,%60,%61,%62,%63,"
    "%64,%65,%66,%67,%68,%69,%70,%71,%72,%73,%74,%75,%76,%77,%78,%79,%80,%81,%82,%83,%84,%85,%86,%87,%88,%89,%90,%91,%92,%93,%94,%95,"
    "%96,%97,%98,%99,%100,%101,%102,%103,%104,%105,%106,%107,%108,%109,%110,%111,%112,%113,%114,%115,%116,%117,%118,%119,%120,%121,%122,%123,%124,%125,%126,%127"
    "}, %128, %129, p, 1, 1, 0, 1;\n}"
    : "+f"(c[0]), "+f"(c[1]), "+f"(c[2]), "+f"(c[3]), "+f"(c[4]), "+f"(c[5]), "+f"(c[6]), "+f"(c[7]),
      "+f"(c[8]), "+f"(c[9]), "+f"(c[10]), "+f"(c[11]), "+f"(c[12]), "+f"(c[13]), "+f"(c[14]), "+f"(c[15]),
      "+f"(c[16]), "+f"(c[17]), "+f"(c[18]), "+f"(c[19]), "+f"(c[20]), "+f"(c[21]), "+f"(c[22]), "+f"(c[23]),
      "+f"(c[24]), "+f"(c[25]), "+f"(c[26]), "+f"(c[27]), "+f"(c[28]), "+f"(c[29]), "+f"(c[30]), "+f"(c[31]),
      "+f"(c[32]), "+f"(c[33]), "+f"(c[34]), "+f"(c[35]), "+f"(c[36]), "+f"(c[37]), "+f"(c[38]), "+f"(c[39]),
      "+f"(c[40]), "+f"(c[41]), "+f"(c[42]), "+f"(c[43]), "+f"(c[44]), "+f"(c[45]), "+f"(c[46]), "+f"(c[47]),
      "+f"(c[48]), "+f"(c[49]), "+f"(c[50]), "+f"(c[51]), "+f"(c[52]), "+f"(c[53]), "+f"(c[54]), "+f"(c[55]),
      "+f"(c[56]), "+f"(c[57]), "+f"(c[58]), "+f"(c[59]), "+f"(c[60]), "+f"(c[61]), "+f"(c[62]), "+f"(c[63]),
      "+f"(c[64]), "+f"(c[65]), "+f"(c[66]), "+f"(c[67]), "+f"(c[68]), "+f"(c[69]), "+f"(c[70]), "+f"(c[71]),
      "+f"(c[72]), "+f"(c[73]), "+f"(c[74]), "+f"(c[75]), "+f"(c[76]), "+f"(c[77]), "+f"(c[78]), "+f"(c[79]),
      "+f"(c[80]), "+f"(c[81]), "+f"(c[82]), "+f"(c[83]), "+f"(c[84]), "+f"(c[85]), "+f"(c[86]), "+f"(c[87]),
      "+f"(c[88]), "+f"(c[89]), "+f"(c[90]), "+f"(c[91]), "+f"(c[92]), "+f"(c[93]), "+f"(c[94]), "+f"(c[95]),
      "+f"(c[96]), "+f"(c[97]), "+f"(c[98]), "+f"(c[99]), "+f"(c[100]), "+f"(c[101]), "+f"(c[102]), "+f"(c[103]),
      "+f"(c[104]), "+f"(c[105]), "+f"(c[106]), "+f"(c[107]), "+f"(c[108]), "+f"(c[109]), "+f"(c[110]), "+f"(c[111]),
      "+f"(c[112]), "+f"(c[113]), "+f"(c[114]), "+f"(c[115]), "+f"(c[116]), "+f"(c[117]), "+f"(c[118]), "+f"(c[119]),
      "+f"(c[120]), "+f"(c[121]), "+f"(c[122]), "+f"(c[123]), "+f"(c[124]), "+f"(c[125]), "+f"(c[126]), "+f"(c[127])
    : "l"(da), "l"(db), "r"(acc));
}

__global__ void __launch_bounds__(384, 1)
k_gemm(const __grid_constant__ CUtensorMap tmG, const __grid_constant__ CUtensorMap tmU, const __grid_constant__ CUtensorMap tmD,
       const __grid_constant__ CUtensorMap tmO, const __nv_bfloat16* __restrict__ x, __nv_bfloat16* __restrict__ out, int mode) {
  extern __shared__ __align__(1024) unsigned char smem[];
  const uint32_t sb = smem_u32(smem);
  const int tid = threadIdx.x, lane = tid & 31, warp = tid >> 5;
  const uint32_t fullb = sb + G_SM_BAR, emptyb = fullb + 8 * G_STAGES;
  if (tid == 0) {
    for (int i = 0; i < G_STAGES; i++) { mbar_init(fullb + 8 * i, 1); mbar_init(emptyb + 8 * i, 2); }
    asm volatile("fence.mbarrier_init.release.cluster;" ::: "memory");
  }
  __syncthreads();
  const int nitems = mode == 0 ? 176 : 32;
  const int nk = mode == 0 ? 8 : HCH + 64;
  if (warp < 4) {
    reg_dec<40>();
    if (tid == 0) {
      int st = 0, ph = 0;
      for (int item = blockIdx.x; item < nitems; item += gridDim.x) {
        const int blk = mode == 0 ? item / 11 : item >> 1, nt = mode == 0 ? item % 11 : item & 1;
        for (int kc = 0; kc < nk; kc++) {
          mbar_wait(emptyb + 8 * st, ph ^ 1);
          const uint32_t sa = sb + st * G_STAGE_BYTES, bar = fullb + 8 * st;
          mbar_arrive_tx(bar, G_STAGE_BYTES);
          if (mode == 0) {
            bulk_g2s(sa, g_xn + ((size_t)kc * S_TOK + blk * 128) * 128, 16384, bar);
            tma2d(sa + 16384, &tmG, nt * 128, kc * 64, bar);
            tma2d(sa + 16384 + 8192, &tmG, nt * 128 + 64, kc * 64, bar);
            tma2d(sa + 16384 + 16384, &tmU, nt * 128, kc * 64, bar);
            tma2d(sa + 16384 + 24576, &tmU, nt * 128 + 64, kc * 64, bar);
          } else {
            const bool hp = kc < HCH;
            const unsigned char* asrc = hp ? g_h + ((size_t)kc * S_TOK + blk * 128) * 128 : g_ox + ((size_t)(kc - HCH) * S_TOK + blk * 128) * 128;
            bulk_g2s(sa, asrc, 16384, bar);
            const CUtensorMap* m = hp ? &tmD : &tmO;
            const int kr = (hp ? kc : kc - HCH) * 64;
#pragma unroll
            for (int i = 0; i < 4; i++) tma2d(sa + 16384 + i * 8192, m, nt * 256 + i * 64, kr, bar);
          }
          if (++st == G_STAGES) { st = 0; ph ^= 1; }
        }
      }
    }
  } else {
    reg_inc<232>();
    const int wg = (warp >> 2) - 1;
    float c[128];
    int st = 0, ph = 0;
    for (int item = blockIdx.x; item < nitems; item += gridDim.x) {
      const int blk = mode == 0 ? item / 11 : item >> 1, nt = mode == 0 ? item % 11 : item & 1;
      int prev = -1;
      for (int kc = 0; kc < nk; kc++) {
        mbar_wait(fullb + 8 * st, ph);
        const uint32_t sa = sb + st * G_STAGE_BYTES;
        wg_fence();
#pragma unroll
        for (int ks = 0; ks < 4; ks++)
          wgmma_ss_n256(c, mkdesc(sa + wg * 8192 + ks * 32, 16, 1024), mkdesc(sa + 16384 + ks * 2048, 8192, 1024), kc | ks);
        wg_commit();
        if (prev >= 0) { wg_wait<1>(); if ((tid & 127) == 0) mbar_arrive(emptyb + 8 * prev); }
        prev = st;
        if (++st == G_STAGES) { st = 0; ph ^= 1; }
      }
      wg_wait<0>();
      if ((tid & 127) == 0) mbar_arrive(emptyb + 8 * prev);
      const int wr = (warp & 3) * 16;
      if (mode == 0) {
        const uint32_t stg = sb + G_SM_BAR + 1024 + wg * 16384;
        if ((tid & 127) == 0) bulk_wait_read();
        bar_sync(1 + wg, 128);
        const int row = wr + (lane & 7) + ((lane >> 3) & 1) * 8;
#pragma unroll
        for (int np = 0; np < 8; np++) {
          uint32_t r[4];
#pragma unroll
          for (int t = 0; t < 2; t++) {
            const int i = (2 * np + t) * 4;
            r[2 * t] = pack_bf16(bfr(c[i]) * bfr(c[64 + i]), bfr(c[i + 1]) * bfr(c[64 + i + 1]));
            r[2 * t + 1] = pack_bf16(bfr(c[i + 2]) * bfr(c[64 + i + 2]), bfr(c[i + 3]) * bfr(c[64 + i + 3]));
          }
          const int c16 = 2 * np + (lane >> 4);
          stsm4(stg + (c16 >> 3) * 8192 + row * 128 + (((c16 & 7) ^ (row & 7)) << 4), r[0], r[1], r[2], r[3]);
        }
        fence_async_smem();
        bar_sync(1 + wg, 128);
        if ((tid & 127) == 0) {
          unsigned char* dst = g_h + ((size_t)(nt * 2) * S_TOK + blk * 128 + wg * 64) * 128;
          bulk_s2g(dst, stg, 8192);
          bulk_s2g(dst + (size_t)S_TOK * 128, stg + 8192, 8192);
          bulk_commit();
        }
      } else {
        const int r0 = blk * 128 + wg * 64 + wr + (lane >> 2);
        const int c0 = nt * 256 + (lane & 3) * 2;
#pragma unroll
        for (int i = 0; i < 32; i++) {
          const size_t o0 = (size_t)r0 * DM + c0 + i * 8, o1 = o0 + 8 * DM;
          const uint32_t x0 = *reinterpret_cast<const uint32_t*>(x + o0), x1 = *reinterpret_cast<const uint32_t*>(x + o1);
          *reinterpret_cast<uint32_t*>(out + o0) = pack_bf16(bf_lo(x0) + c[4 * i], bf_hi(x0) + c[4 * i + 1]);
          *reinterpret_cast<uint32_t*>(out + o1) = pack_bf16(bf_lo(x1) + c[4 * i + 2], bf_hi(x1) + c[4 * i + 3]);
        }
      }
    }
    if ((tid & 127) == 0) bulk_wait_all();
  }
}

typedef CUresult (*EncodeFn)(CUtensorMap*, CUtensorMapDataType, cuuint32_t, void*, const cuuint64_t*, const cuuint64_t*,
                             const cuuint32_t*, const cuuint32_t*, CUtensorMapInterleave, CUtensorMapSwizzle,
                             CUtensorMapL2promotion, CUtensorMapFloatOOBfill);

void make_map(EncodeFn fn, CUtensorMap* m, const void* p, int rows, int cols) {
  cuuint64_t dims[2] = {(cuuint64_t)cols, (cuuint64_t)rows};
  cuuint64_t strides[1] = {(cuuint64_t)cols * 2};
  cuuint32_t box[2] = {64, 64}, es[2] = {1, 1};
  fn(m, CU_TENSOR_MAP_DATA_TYPE_BFLOAT16, 2, const_cast<void*>(p), dims, strides, box, es, CU_TENSOR_MAP_INTERLEAVE_NONE,
     CU_TENSOR_MAP_SWIZZLE_128B, CU_TENSOR_MAP_L2_PROMOTION_L2_256B, CU_TENSOR_MAP_FLOAT_OOB_FILL_NONE);
}

}

extern "C" void kernel_launch(void* const* d_in, const int* in_sizes, int n_in, void* d_out, int out_size) {
  (void)in_sizes; (void)n_in; (void)out_size;
  const __nv_bfloat16* x = (const __nv_bfloat16*)d_in[0];
  const __nv_bfloat16* mem0 = (const __nv_bfloat16*)d_in[1];
  const __nv_bfloat16* Wq = (const __nv_bfloat16*)d_in[2];
  const __nv_bfloat16* Wk = (const __nv_bfloat16*)d_in[3];
  const __nv_bfloat16* Wv = (const __nv_bfloat16*)d_in[4];
  const __nv_bfloat16* Wo = (const __nv_bfloat16*)d_in[5];
  __nv_bfloat16* out = (__nv_bfloat16*)d_out;

  static EncodeFn enc = nullptr;
  if (!enc) {
    void* fn = nullptr; cudaDriverEntryPointQueryResult qr;
    cudaGetDriverEntryPoint("cuTensorMapEncodeTiled", &fn, cudaEnableDefault, &qr);
    enc = (EncodeFn)fn;
    cudaFuncSetAttribute(k_chain, cudaFuncAttributeMaxDynamicSharedMemorySize, SM_END);
    cudaFuncSetAttribute(k_gemm, cudaFuncAttributeMaxDynamicSharedMemorySize, G_SM_END);
  }
  CUtensorMap tmG, tmU, tmD, tmO;
  make_map(enc, &tmG, d_in[8], DM, FF);
  make_map(enc, &tmU, d_in[9], DM, FF);
  make_map(enc, &tmD, d_in[10], FF, DM);
  make_map(enc, &tmO, Wo, NH * DH, DM);

  cudaStream_t st = cudaStreamPerThread;
  k_ln<<<256, 256, 0, st>>>(x);
  {
    cudaLaunchConfig_t cfg = {};
    cfg.gridDim = dim3(NCL * CLS); cfg.blockDim = dim3(512); cfg.dynamicSmemBytes = SM_END; cfg.stream = st;
    cudaLaunchAttribute at[2];
    at[0].id = cudaLaunchAttributeClusterDimension; at[0].val.clusterDim.x = CLS; at[0].val.clusterDim.y = 1; at[0].val.clusterDim.z = 1;
    at[1].id = cudaLaunchAttributeProgrammaticStreamSerialization; at[1].val.programmaticStreamSerializationAllowed = 1;
    cfg.attrs = at; cfg.numAttrs = 2;
    cudaLaunchKernelEx(&cfg, k_chain, mem0, Wq, Wk, Wv, Wo);
  }
  k_gemm<<<132, 384, G_SM_END, st>>>(tmG, tmU, tmD, tmO, x, out, 0);
  k_gemm<<<32, 384, G_SM_END, st>>>(tmG, tmU, tmD, tmO, x, out, 1);
}
```

```cpp
#include <cuda_runtime.h>
#include <cuda_bf16.h>
#include <cuda_fp16.h>
#include <cuda.h>
#include <stdint.h>

namespace {

constexpr int S_TOK = 2048, DM = 512, NH = 32, DH = 128, NSEG = 64, FF = 1376;
constexpr int NCL = 16, CLS = 6;
constexpr int NHELP = 36;
constexpr int NCTA = NCL * CLS + NHELP;
constexpr int NVST = 4;
constexpr int HCH = 22;

__device__ __align__(1024) unsigned char g_xn[8 * S_TOK * 128];
__device__ __align__(1024) unsigned char g_ox[64 * S_TOK * 128];
__device__ __align__(1024) unsigned char g_h[HCH * S_TOK * 128];
__device__ __align__(1024) unsigned char g_q[8 * NH * 8192];
__device__ __align__(1024) unsigned char g_k[8 * NH * 8192];
__device__ __align__(1024) unsigned char g_v[4 * NCL * 16384];
constexpr int EX_WARP = 1024, EX_RANK = 4 * EX_WARP, EX_BUF = CLS * EX_RANK;
__device__ __align__(1024) unsigned char g_ex[4 * EX_BUF];
__device__ __align__(1024) unsigned char g_acc[NSEG * 32 * 1536];
__device__ __align__(1024) float g_ffn[S_TOK * DM];
__device__ unsigned int g_done;
__device__ unsigned int g_ln0;
__device__ unsigned int g_lncnt;
__device__ __align__(16) unsigned int g_cnt[8 * NSEG];
__device__ unsigned int g_hcnt[16];
__device__ unsigned int g_dcnt[32];
__device__ unsigned int g_err;
#define GT(row, slot) do {} while (0)

__device__ __forceinline__ uint32_t smem_u32(const void* p) { return (uint32_t)__cvta_generic_to_shared(p); }
__device__ __forceinline__ uint32_t mapa(uint32_t a, uint32_t r) {
  uint32_t o; asm volatile("mapa.shared::cluster.u32 %0, %1, %2;" : "=r"(o) : "r"(a), "r"(r)); return o;
}
__device__ __forceinline__ void mbar_init(uint32_t bar, uint32_t cnt) {
  asm volatile("mbarrier.init.shared::cta.b64 [%0], %1;" ::"r"(bar), "r"(cnt) : "memory");
}
__device__ __forceinline__ void mbar_arrive(uint32_t bar) {
  asm volatile("mbarrier.arrive.shared::cta.b64 _, [%0];" ::"r"(bar) : "memory");
}
__device__ __forceinline__ void mbar_arrive_tx(uint32_t bar, uint32_t bytes) {
  asm volatile("mbarrier.arrive.expect_tx.shared::cta.b64 _, [%0], %1;" ::"r"(bar), "r"(bytes) : "memory");
}
__device__ __forceinline__ void mbar_arrive_remote(uint32_t cbar) {
  asm volatile("mbarrier.arrive.shared::cluster.b64 _, [%0];" ::"r"(cbar) : "memory");
}
__device__ __forceinline__ void mbar_arrive_remote_rel(uint32_t cbar) {
  asm volatile("mbarrier.arrive.release.cluster.shared::cluster.b64 _, [%0];" ::"r"(cbar) : "memory");
}
__device__ __forceinline__ bool mbar_try(uint32_t bar, uint32_t par) {
  uint32_t ok;
  asm volatile("{\n.reg .pred p;\nmbarrier.try_wait.parity.shared::cta.b64 p, [%1], %2;\nselp.u32 %0, 1, 0, p;\n}"
               : "=r"(ok) : "r"(bar), "r"(par) : "memory");
  return ok;
}
__device__ __forceinline__ bool mbar_try_t(uint32_t bar, uint32_t par) {
  uint32_t ok;
  asm volatile("{\n.reg .pred p;\nmbarrier.try_wait.parity.shared::cta.b64 p, [%1], %2, 1000;\nselp.u32 %0, 1, 0, p;\n}"
               : "=r"(ok) : "r"(bar), "r"(par) : "memory");
  return ok;
}
__device__ __forceinline__ bool mbar_try_acq(uint32_t bar, uint32_t par) {
  uint32_t ok;
  asm volatile("{\n.reg .pred p;\nmbarrier.try_wait.parity.acquire.cluster.shared::cta.b64 p, [%1], %2;\nselp.u32 %0, 1, 0, p;\n}"
               : "=r"(ok) : "r"(bar), "r"(par) : "memory");
  return ok;
}
__device__ __forceinline__ uint32_t clk32m() { uint32_t c; asm volatile("mov.u32 %0, %%clock;" : "=r"(c) :: "memory"); return c; }
__device__ __forceinline__ uint32_t clk32() { uint32_t c; asm volatile("mov.u32 %0, %%clock;" : "=r"(c)); return c; }
__device__ __forceinline__ void mbar_wait(uint32_t bar, uint32_t par) {
  asm volatile("{\n.reg .pred p, q;\n.reg .b32 c;\nmov.b32 c, 0;\nLW:\n"
               "mbarrier.try_wait.parity.shared::cta.b64 p, [%0], %1;\n"
               "add.u32 c, c, 1;\nsetp.lt.and.u32 q, c, 4096, !p;\n@q bra LW;\n}" ::"r"(bar), "r"(par) : "memory");
}
__device__ __forceinline__ void mbar_hint(uint32_t bar, uint32_t par) {
  const uint32_t t0 = clk32();
  while (!mbar_try_t(bar, par) && clk32() - t0 < 4000) {}
}
__device__ __forceinline__ void mbar_arrive_tx_if(uint32_t bar, uint32_t bytes, bool pred) {
  asm volatile("{\n.reg .pred p;\nsetp.ne.b32 p, %2, 0;\n@p mbarrier.arrive.expect_tx.shared::cta.b64 _, [%0], %1;\n}"
               ::"r"(bar), "r"(bytes), "r"((int)pred) : "memory");
}
__device__ __forceinline__ void bar_sync_if(int id, int n, bool pred) {
  asm volatile("{\n.reg .pred p;\nsetp.ne.b32 p, %2, 0;\n@p bar.sync %0, %1;\n}" ::"r"(id), "r"(n), "r"((int)pred) : "memory");
}
__device__ __forceinline__ void bar_arrive_if(int id, int n, bool pred) {
  asm volatile("{\n.reg .pred p;\nsetp.ne.b32 p, %2, 0;\n@p bar.arrive %0, %1;\n}" ::"r"(id), "r"(n), "r"((int)pred) : "memory");
}
__device__ __forceinline__ void mbar_wait_acq(uint32_t bar, uint32_t par) {
  mbar_wait(bar, par);
  (void)mbar_try_acq(bar, par);
}
__device__ __forceinline__ void st_async32(uint32_t caddr, uint32_t v, uint32_t cbar) {
  asm volatile("st.async.weak.shared::cluster.mbarrier::complete_tx::bytes.b32 [%0], %1, [%2];" ::"r"(caddr), "r"(v), "r"(cbar) : "memory");
}
__device__ __forceinline__ void sts32(uint32_t a, uint32_t v) { asm volatile("st.shared.b32 [%0], %1;" ::"r"(a), "r"(v) : "memory"); }
__device__ __forceinline__ uint32_t lds32(uint32_t a) { uint32_t v; asm volatile("ld.shared.b32 %0, [%1];" : "=r"(v) : "r"(a) : "memory"); return v; }
__device__ __forceinline__ void sts128(uint32_t a, uint32_t x, uint32_t y, uint32_t z, uint32_t w) {
  asm volatile("st.shared.v4.b32 [%0], {%1,%2,%3,%4};" ::"r"(a), "r"(x), "r"(y), "r"(z), "r"(w) : "memory");
}
__device__ __forceinline__ void lds128(uint32_t a, uint32_t* r) {
  asm volatile("ld.shared.v4.b32 {%0,%1,%2,%3}, [%4];" : "=r"(r[0]), "=r"(r[1]), "=r"(r[2]), "=r"(r[3]) : "r"(a) : "memory");
}
__device__ __forceinline__ void ldsm4(uint32_t a, uint32_t* r) {
  asm volatile("ldmatrix.sync.aligned.m8n8.x4.shared.b16 {%0,%1,%2,%3}, [%4];" : "=r"(r[0]), "=r"(r[1]), "=r"(r[2]), "=r"(r[3]) : "r"(a) : "memory");
}
__device__ __forceinline__ void ldsm4t(uint32_t a, uint32_t* r) {
  asm volatile("ldmatrix.sync.aligned.m8n8.x4.trans.shared.b16 {%0,%1,%2,%3}, [%4];" : "=r"(r[0]), "=r"(r[1]), "=r"(r[2]), "=r"(r[3]) : "r"(a) : "memory");
}
__device__ __forceinline__ void ldsm2(uint32_t a, uint32_t* r) {
  asm volatile("ldmatrix.sync.aligned.m8n8.x2.shared.b16 {%0,%1}, [%2];" : "=r"(r[0]), "=r"(r[1]) : "r"(a) : "memory");
}
__device__ __forceinline__ void ldsm2t(uint32_t a, uint32_t* r) {
  asm volatile("ldmatrix.sync.aligned.m8n8.x2.trans.shared.b16 {%0,%1}, [%2];" : "=r"(r[0]), "=r"(r[1]) : "r"(a) : "memory");
}
__device__ __forceinline__ void stsm4(uint32_t a, uint32_t r0, uint32_t r1, uint32_t r2, uint32_t r3) {
  asm volatile("stmatrix.sync.aligned.m8n8.x4.shared.b16 [%0], {%1,%2,%3,%4};" ::"r"(a), "r"(r0), "r"(r1), "r"(r2), "r"(r3) : "memory");
}
__device__ __forceinline__ void stsm4t(uint32_t a, uint32_t r0, uint32_t r1, uint32_t r2, uint32_t r3) {
  asm volatile("stmatrix.sync.aligned.m8n8.x4.trans.shared.b16 [%0], {%1,%2,%3,%4};" ::"r"(a), "r"(r0), "r"(r1), "r"(r2), "r"(r3) : "memory");
}
__device__ __forceinline__ void stsm2t(uint32_t a, uint32_t r0, uint32_t r1) {
  asm volatile("stmatrix.sync.aligned.m8n8.x2.trans.shared.b16 [%0], {%1,%2};" ::"r"(a), "r"(r0), "r"(r1) : "memory");
}
__device__ __forceinline__ void mma16816(float* c, const uint32_t* a, uint32_t b0, uint32_t b1) {
  asm volatile("mma.sync.aligned.m16n8k16.row.col.f32.bf16.bf16.f32 {%0,%1,%2,%3}, {%4,%5,%6,%7}, {%8,%9}, {%0,%1,%2,%3};"
               : "+f"(c[0]), "+f"(c[1]), "+f"(c[2]), "+f"(c[3]) : "r"(a[0]), "r"(a[1]), "r"(a[2]), "r"(a[3]), "r"(b0), "r"(b1));
}
__device__ __forceinline__ void mma16816r(float* c, uint32_t a0, uint32_t a1, uint32_t a2, uint32_t a3, uint32_t b0, uint32_t b1) {
  asm volatile("mma.sync.aligned.m16n8k16.row.col.f32.bf16.bf16.f32 {%0,%1,%2,%3}, {%4,%5,%6,%7}, {%8,%9}, {%0,%1,%2,%3};"
               : "+f"(c[0]), "+f"(c[1]), "+f"(c[2]), "+f"(c[3]) : "r"(a0), "r"(a1), "r"(a2), "r"(a3), "r"(b0), "r"(b1));
}
__device__ __forceinline__ void mma1688(float* c, uint32_t a0, uint32_t a1, uint32_t b0) {
  asm volatile("mma.sync.aligned.m16n8k8.row.col.f32.bf16.bf16.f32 {%0,%1,%2,%3}, {%4,%5}, {%6}, {%0,%1,%2,%3};"
               : "+f"(c[0]), "+f"(c[1]), "+f"(c[2]), "+f"(c[3]) : "r"(a0), "r"(a1), "r"(b0));
}
__device__ __forceinline__ uint32_t pack_bf16(float lo, float hi) {
  uint32_t r; asm("cvt.rn.bf16x2.f32 %0, %1, %2;" : "=r"(r) : "f"(hi), "f"(lo)); return r;
}
__device__ __forceinline__ uint32_t pack_f16(float lo, float hi) {
  uint32_t r; asm("cvt.rn.f16x2.f32 %0, %1, %2;" : "=r"(r) : "f"(hi), "f"(lo)); return r;
}
__device__ __forceinline__ uint32_t f16_to_bf16(uint32_t h) {
  float lo, hi;
  asm("{\n.reg .b16 l, h;\nmov.b32 {l, h}, %2;\ncvt.f32.f16 %0, l;\ncvt.f32.f16 %1, h;\n}" : "=f"(lo), "=f"(hi) : "r"(h));
  uint32_t r; asm("cvt.rn.bf16x2.f32 %0, %1, %2;" : "=r"(r) : "f"(hi), "f"(lo)); return r;
}
__device__ __forceinline__ float bf_lo(uint32_t w) { return __uint_as_float(w << 16); }
__device__ __forceinline__ float bf_hi(uint32_t w) { return __uint_as_float(w & 0xffff0000u); }
__device__ __forceinline__ float ex2(float x) { float y; asm("ex2.approx.ftz.f32 %0, %1;" : "=f"(y) : "f"(x)); return y; }
__device__ __forceinline__ float rcp(float x) { float y; asm("rcp.approx.ftz.f32 %0, %1;" : "=f"(y) : "f"(x)); return y; }
__device__ __forceinline__ void bar_sync(int id, int n) { asm volatile("bar.sync %0, %1;" ::"r"(id), "r"(n) : "memory"); }
__device__ __forceinline__ void bar_arrive(int id, int n) { asm volatile("bar.arrive %0, %1;" ::"r"(id), "r"(n) : "memory"); }
__device__ __forceinline__ void fence_async_smem() { asm volatile("fence.proxy.async.shared::cta;" ::: "memory"); }
__device__ __forceinline__ void fence_async_all() { asm volatile("fence.proxy.async.global;" ::: "memory"); }
__device__ __forceinline__ void cp_async16(uint32_t dst, const void* src) {
  asm volatile("cp.async.cg.shared.global [%0], [%1], 16;" ::"r"(dst), "l"(src) : "memory");
}
__device__ __forceinline__ void cp_async16p(uint32_t dst, const void* src) {
  asm volatile("cp.async.cg.shared.global.L2::128B [%0], [%1], 16;" ::"r"(dst), "l"(src) : "memory");
}
__device__ __forceinline__ void prefetch_l2(const void* src, uint32_t bytes) {
  asm volatile("cp.async.bulk.prefetch.L2.global [%0], %1;" ::"l"(src), "r"(bytes) : "memory");
}
__device__ __forceinline__ void cp_async_wait_all() { asm volatile("cp.async.wait_all;" ::: "memory"); }
__device__ __forceinline__ void bulk_g2s(uint32_t dst, const void* src, uint32_t bytes, uint32_t bar) {
  asm volatile("cp.async.bulk.shared::cluster.global.mbarrier::complete_tx::bytes [%0], [%1], %2, [%3];"
               ::"r"(dst), "l"(src), "r"(bytes), "r"(bar) : "memory");
}
__device__ __forceinline__ void bulk_g2s_mc(uint32_t dst, const void* src, uint32_t bytes, uint32_t bar, uint16_t mask) {
  asm volatile("cp.async.bulk.shared::cluster.global.mbarrier::complete_tx::bytes.multicast::cluster [%0], [%1], %2, [%3], %4;"
               ::"r"(dst), "l"(src), "r"(bytes), "r"(bar), "h"(mask) : "memory");
}
__device__ __forceinline__ void bulk_s2g(void* dst, uint32_t src, uint32_t bytes) {
  asm volatile("cp.async.bulk.global.shared::cta.bulk_group [%0], [%1], %2;" ::"l"(dst), "r"(src), "r"(bytes) : "memory");
}
__device__ __forceinline__ void bulk_commit() { asm volatile("cp.async.bulk.commit_group;" ::: "memory"); }
__device__ __forceinline__ void bulk_wait_read() { asm volatile("cp.async.bulk.wait_group.read 0;" ::: "memory"); }
__device__ __forceinline__ void bulk_wait_all() { asm volatile("cp.async.bulk.wait_group 0;" ::: "memory"); }
__device__ __forceinline__ void tma2d(uint32_t dst, const CUtensorMap* m, int c0, int c1, uint32_t bar) {
  asm volatile("cp.async.bulk.tensor.2d.shared::cluster.global.mbarrier::complete_tx::bytes [%0], [%1, {%3, %4}], [%2];"
               ::"r"(dst), "l"(m), "r"(bar), "r"(c0), "r"(c1) : "memory");
}
__device__ __forceinline__ void pdl_wait() { asm volatile("griddepcontrol.wait;" ::: "memory"); }
__device__ __forceinline__ void pdl_launch() { asm volatile("griddepcontrol.launch_dependents;" ::: "memory"); }
__device__ __forceinline__ void cluster_sync() {
  asm volatile("barrier.cluster.arrive.aligned;\nbarrier.cluster.wait.aligned;" ::: "memory");
}
__device__ __forceinline__ void cluster_arrive_rlx() { asm volatile("barrier.cluster.arrive.relaxed.aligned;" ::: "memory"); }
__device__ __forceinline__ void cluster_wait() { asm volatile("barrier.cluster.wait.aligned;" ::: "memory"); }
__device__ __forceinline__ void red_release(unsigned int* p) {
  asm volatile("red.release.gpu.global.add.u32 [%0], 1;" ::"l"(p) : "memory");
}
__device__ __forceinline__ void poll_ge(const unsigned int* p, unsigned int v) {
  for (int it = 0; it < 30000; it++) {
    unsigned int r;
    asm volatile("ld.acquire.gpu.global.u32 %0, [%1];" : "=r"(r) : "l"(p) : "memory");
    if ((int)(r - v) >= 0) return;
  }
  *(volatile unsigned int*)&g_err = 3;
}
__device__ __forceinline__ uint64_t mkdesc(uint32_t saddr, uint32_t lbo, uint32_t sbo) {
  return (uint64_t)((saddr & 0x3FFFF) >> 4) | ((uint64_t)(lbo >> 4) << 16) | ((uint64_t)(sbo >> 4) << 32) | ((uint64_t)1 << 62);
}
__device__ __forceinline__ void wg_fence() { asm volatile("wgmma.fence.sync.aligned;" ::: "memory"); }
__device__ __forceinline__ void wg_commit() { asm volatile("wgmma.commit_group.sync.aligned;" ::: "memory"); }
template <int N> __device__ __forceinline__ void wg_wait() { asm volatile("wgmma.wait_group.sync.aligned %0;" ::"n"(N) : "memory"); }
__device__ __forceinline__ void wgmma_rs_n32(float* c, const uint32_t* a, uint64_t d, int acc) {
  asm volatile("{\n.reg .pred p;\nsetp.ne.b32 p, %21, 0;\n"
    "wgmma.mma_async.sync.aligned.m64n32k16.f32.bf16.bf16 {%0,%1,%2,%3,%4,%5,%6,%7,%8,%9,%10,%11,%12,%13,%14,%15}, {%16,%17,%18,%19}, %20, p, 1, 1, 0;\n}"
    : "+f"(c[0]), "+f"(c[1]), "+f"(c[2]), "+f"(c[3]), "+f"(c[4]), "+f"(c[5]), "+f"(c[6]), "+f"(c[7]),
      "+f"(c[8]), "+f"(c[9]), "+f"(c[10]), "+f"(c[11]), "+f"(c[12]), "+f"(c[13]), "+f"(c[14]), "+f"(c[15])
    : "r"(a[0]), "r"(a[1]), "r"(a[2]), "r"(a[3]), "l"(d), "r"(acc));
}
template <int R> __device__ __forceinline__ void reg_inc() { asm volatile("setmaxnreg.inc.sync.aligned.u32 %0;" ::"n"(R)); }
template <int R> __device__ __forceinline__ void reg_dec() { asm volatile("setmaxnreg.dec.sync.aligned.u32 %0;" ::"n"(R)); }

#define PROF_T(slot) do {} while (0)

#define BB_FENCE(K) asm volatile("{\n.reg .pred p;\nsetp.eq.s32 p, %0, %1;\n@p trap;\n}" ::"r"(zu), "n"(ZK + (K)) : "memory")
#define AFENCE(K) do {} while (0)
#define PIN(x) asm volatile("" : "+r"(x))

#define PFN 4
__device__ __forceinline__ float bfr(float x) { return __bfloat162float(__float2bfloat16_rn(x)); }

__device__ __forceinline__ void ln_row(uint4& v0, uint4& v1) {
  float f[16];
  {
    uint32_t w[8] = {v0.x, v0.y, v0.z, v0.w, v1.x, v1.y, v1.z, v1.w};
#pragma unroll
    for (int i = 0; i < 8; i++) { f[2 * i] = bf_lo(w[i]); f[2 * i + 1] = bf_hi(w[i]); }
  }
  float sum = 0.f;
#pragma unroll
  for (int i = 0; i < 16; i++) sum += f[i];
#pragma unroll
  for (int o = 16; o; o >>= 1) sum += __shfl_xor_sync(0xffffffffu, sum, o);
  const float mean = sum * (1.f / DM);
  float sq = 0.f;
#pragma unroll
  for (int i = 0; i < 16; i++) { float d = f[i] - mean; sq += d * d; }
#pragma unroll
  for (int o = 16; o; o >>= 1) sq += __shfl_xor_sync(0xffffffffu, sq, o);
  const float mb = bfr(mean), vb = bfr(sq * (1.f / DM));
  const float rs = 1.f / bfr(sqrtf(bfr(vb + 1e-5f)));
  uint32_t o[8];
#pragma unroll
  for (int i = 0; i < 8; i++) {
    const uint32_t d = pack_bf16(f[2 * i] - mb, f[2 * i + 1] - mb);
    o[i] = pack_bf16(bf_lo(d) * rs, bf_hi(d) * rs);
  }
  v0 = make_uint4(o[0], o[1], o[2], o[3]);
  v1 = make_uint4(o[4], o[5], o[6], o[7]);
}

constexpr int SM_BAR = 0;
constexpr int SM_XN = 1024;
constexpr int SM_WO = SM_XN + 32768;
constexpr int SM_MEM = SM_WO + 4096;
constexpr int SM_ATQ = SM_WO + 12288 + 4096;
constexpr int SM_ATK = SM_WO + 2 * 12288 + 4096;
constexpr int SM_OX = SM_WO + 3 * 12288 + 4096;
constexpr int SM_STG = SM_WO + 49152;
constexpr int SM_V = SM_STG;
constexpr int SM_VM = SM_V + NVST * 16384;
constexpr int SM_KX = SM_VM + 4 * 4096;
constexpr int KX_SLOT = 8192 + 1536;
constexpr int SM_KMA = SM_KX + 3 * KX_SLOT;
constexpr int SM_SC = SM_KMA + 2 * 2048;
constexpr int SM_O = SM_SC + 4096;
constexpr int SM_PAIR = SM_O + 4096;
constexpr int SM_LI = SM_PAIR + 1024;
constexpr int SM_SCR = SM_LI + 256;
constexpr int SM_WX = SM_SCR + 4096;
constexpr int SM_PROF = SM_STG + 131072;
static_assert(SM_WX + 2048 <= SM_PROF, "staging");
constexpr int SM_END = SM_PROF;
static_assert(SM_END <= 232448, "smem");
static_assert(SM_XN % 1024 == 0 && SM_OX % 1024 == 0, "align");
constexpr int B_MEM = 0;
constexpr int B_SC = 3;
constexpr int B_VM = 4;
constexpr int B_XNF = 8;
constexpr int B_XNE = 9;
constexpr int B_VF = 10;
constexpr int B_VE = 14;
constexpr int B_STF = 18;
constexpr int B_STE = 19;
constexpr int B_ATF = 20;
constexpr int B_KMF = 21;
constexpr int B_QKR = 23;
constexpr int B_WL = 32;
constexpr int B_WO = 29;
constexpr int B_XAF = 25;
constexpr int B_XAE = 26;
constexpr int B_XN1 = 30;
constexpr int B_P3 = 31;
constexpr int SM_EP = 512;
struct WMaps { CUtensorMap q48, k48, q32, k32, v32, v64, o64, o32; };

constexpr float SC_LOG2E = 0.08838834764831845f * 1.4426950408889634f;

#define WL_AHEAD 3
#define WO_AFTER 1
#define H2W 0
#define NE1 16
#define POLL_DELAY 350
#define POLL_GAP 150

__global__ void __launch_bounds__(512, 1)
k_chain(const __grid_constant__ WMaps wm, const __nv_bfloat16* __restrict__ mem0, const __nv_bfloat16* __restrict__ x) {
  extern __shared__ __align__(1024) unsigned char smem[];
  const uint32_t sb = smem_u32(smem);
  const int tid = threadIdx.x, lane = tid & 31;
  const int warp = __shfl_sync(0xffffffffu, tid >> 5, 0);
  const int cl = blockIdx.x / CLS;
  const uint32_t rank = blockIdx.x - cl * CLS;
  const int hl = rank / 3, jj = rank - hl * 3;
  const int head = cl * 2 + hl;
  const int nqk = jj < 2 ? 3 : 2, nv = jj < 2 ? 2 : 4;
  const int qk0 = jj * 3, v0 = jj * 2;
  const int nu = rank < 2 ? 12 : 10;
  const int cb = rank < 2 ? rank * 12 : 24 + (rank - 2) * 10;
  auto BAR = [&](int i) { return sb + SM_BAR + 8 * i; };
#define GTR(v) do {} while (0)
  GTR(gt0);
  auto wload = [&](int i) {
    const uint32_t d = sb + SM_STG + i * 16384;
    mbar_arrive_tx(BAR(B_WL + i), 16384);
    tma2d(d, jj < 2 ? &wm.q48 : &wm.q32, head * DH + qk0 * 16, i * 64, BAR(B_WL + i));
    tma2d(d + nqk * 2048, jj < 2 ? &wm.k48 : &wm.k32, head * DH + qk0 * 16, i * 64, BAR(B_WL + i));
    tma2d(d + nqk * 4096, jj < 2 ? &wm.v32 : &wm.v64, head * DH + v0 * 16, i * 64, BAR(B_WL + i));
  };
  if (tid == 480) {
    for (int i = 0; i < 8; i++) mbar_init(BAR(B_WL + i), 1);
    mbar_init(BAR(B_WO), 1);
    asm volatile("fence.mbarrier_init.release.cluster;" ::: "memory");
    GTR(gt1);
#pragma unroll 1
    for (int i = 0; i < WL_AHEAD; i++) wload(i);
    GTR(gt2);
  }
  pdl_launch();
  if (tid < 171 && blockIdx.x * 171 + tid < 16384)
    asm volatile("prefetch.global.L2 [%0];" ::"l"(x + (size_t)(blockIdx.x * 171 + tid) * 64));
  if (tid == 32) sts32(sb + SM_EP, atomicAdd(&g_done, 1u) / NCTA + 1);
  if (tid == 0) {
    mbar_init(BAR(B_MEM + 0), 4); mbar_init(BAR(B_MEM + 1), 4); mbar_init(BAR(B_MEM + 2), nu - 8);
    mbar_init(BAR(B_SC), 5);
    for (int i = 0; i < 4; i++) mbar_init(BAR(B_VM + i), nv);
    mbar_init(BAR(B_XNF), 1); mbar_init(BAR(B_XNE), 2 * CLS);
    mbar_init(BAR(B_XAF), 1); mbar_init(BAR(B_XAE), 2 * CLS);
    for (int i = 0; i < NVST; i++) { mbar_init(BAR(B_VF + i), 1); mbar_init(BAR(B_VE + i), 4); }
    mbar_init(BAR(B_STF), 8); mbar_init(BAR(B_STE), 1);
    mbar_init(BAR(B_ATF), 1); mbar_init(BAR(B_KMF), 1); mbar_init(BAR(B_KMF + 1), 1);
    mbar_init(BAR(B_QKR), 3); mbar_init(BAR(B_QKR + 1), 3);
    mbar_init(BAR(B_XN1), 1);
    mbar_init(BAR(B_P3), 4 * CLS);
    asm volatile("fence.mbarrier_init.release.cluster;" ::: "memory");
  }
  __syncthreads();
  GTR(gt3);
  cluster_arrive_rlx();
  GTR(gt4);

  auto scores = [&](uint32_t a_q, uint32_t a_k, uint32_t k3, int kg, uint32_t l16) {
    uint32_t qa[6], kb[6];
    qa[4] = qa[5] = kb[4] = kb[5] = 0;
    ldsm4(a_q, qa);
    ldsm4(a_k, kb);
    float c0[4] = {0.f, 0.f, 0.f, 0.f}, c1[4] = {0.f, 0.f, 0.f, 0.f}, c2[4] = {0.f, 0.f, 0.f, 0.f};
    if (nqk == 3) {
      ldsm2(a_q + 512, qa + 4);
      ldsm2(a_k + k3, kb + 4);
    }
    mma16816r(c0, qa[0], 0u, qa[1], 0u, kb[0], kb[1]);
    mma16816r(c1, qa[2], 0u, qa[3], 0u, kb[2], kb[3]);
    if (nqk == 3) mma16816r(c2, qa[4], 0u, qa[5], 0u, kb[4], kb[5]);
    const uint32_t wv = pack_f16((c0[0] + c1[0] + c2[0]) * SC_LOG2E, (c0[1] + c1[1] + c2[1]) * SC_LOG2E);
    const uint32_t a_sc = sb + SM_SC + rank * 640 + kg * 128 + (l16 >> 2);
#pragma unroll
    for (int d = 1; d < CLS; d++) {
      uint32_t t = rank + d; if (t >= CLS) t -= CLS;
      st_async32(mapa(a_sc, t), wv, mapa(BAR(B_SC), t));
      if (d == 1) bar_arrive(9, 288);
    }
    sts32(a_sc, wv);
    __syncwarp();
    mbar_arrive_tx_if(BAR(B_SC), kg == 0 ? 5 * 640 : 0, l16 == 0);
  };
  if (warp < 8) {
    reg_inc<176>();
    uint32_t W[32][4];
    {
      const int kr = (lane & 7) + ((lane >> 4) << 3), ch = (lane >> 3) & 1;
      const int mi = warp < nqk ? 0 : warp < 2 * nqk ? 1 : 2;
      const uint32_t pitch = (mi < 2 ? nqk : nv) * 32;
      uint32_t a0 = kr * pitch + (warp - mi * nqk) * 32 + ch * 16;
      a0 ^= ((a0 >> 7) & (pitch == 96 ? 0u : pitch == 64 ? 3u : 7u)) << 4;
      a0 += sb + SM_STG + mi * nqk * 2048;
      cluster_wait();
#pragma unroll
      for (int q = 0; q < 8; q++) {
        mbar_wait(BAR(B_WL + q), 0);
        if (tid == 0 && (q & 1)) GT(blockIdx.x + 104, 72 + (q >> 1));
#pragma unroll
        for (int ks = 0; ks < 4; ks++) ldsm4t(a0 + q * 16384 + ks * 16 * pitch, W[q * 4 + ks]);
      }
    }
    if (tid == 0) GT(blockIdx.x, 1);
    asm volatile("{\n.reg .b32 t;\nshfl.sync.idx.b32 t, %0, 0, 31, -1;\n}" ::"r"(W[31][3]) : "memory");
    asm volatile("fence.release.sync_restrict::shared::cta.cluster;" ::: "memory");
    cluster_arrive_rlx(); cluster_wait();
    if (tid == 0) GT(blockIdx.x, 2);
    auto opq = [&](uint32_t v) { return (uint32_t)__shfl_sync(0xffffffffu, v, lane); };
    uint32_t l16 = opq(lane * 16);
    const bool isq = warp < nqk, isv = warp >= 2 * nqk;
    const uint32_t x_e = opq(mapa(BAR(B_XNE), 0));
    const int zu = warp;
    constexpr int ZK = -100;
    uint32_t kring = 0;
    uint32_t gring = 0;

#pragma unroll 1
    for (int s_ = -2;; s_++) {
     PIN(l16);
     const int s = __shfl_sync(0xffffffffu, s_, 0);
     const int g = s + 2;
     if (s >= 0) {
      if (s == 0) bar_sync(1, 256);
      if (tid == 0) GT(blockIdx.x, 8 + s);
      const uint32_t par = s & 1, r4 = s & 3;
      float acc[4][4];
#pragma unroll
      for (int i = 0; i < 4; i++) { acc[i][0] = acc[i][1] = acc[i][2] = acc[i][3] = 0.f; }
      const uint32_t ma = sb + SM_MEM + l16;
#define KWAVE(o, f, k0, k1, k2, k3, k4, k5) { uint32_t b[4][4]; \
      ldsm4t(ma + (o), b[0]); ldsm4t(ma + (o) + 512, b[1]); ldsm4t(ma + (o) + 1024, b[2]); ldsm4t(ma + (o) + 1536, b[3]); BB_FENCE(f); \
      mma16816(acc[0], W[k0], b[0][0], b[0][1]); mma16816(acc[1], W[(k0) + 1], b[0][2], b[0][3]); ldsm4t(ma + (o) + 2048, b[0]); BB_FENCE(f + 2); \
      mma16816(acc[2], W[k1], b[1][0], b[1][1]); mma16816(acc[3], W[(k1) + 1], b[1][2], b[1][3]); ldsm4t(ma + (o) + 2560, b[1]); BB_FENCE(f + 4); \
      mma16816(acc[0], W[k2], b[2][0], b[2][1]); mma16816(acc[1], W[(k2) + 1], b[2][2], b[2][3]); \
      mma16816(acc[2], W[k3], b[3][0], b[3][1]); mma16816(acc[3], W[(k3) + 1], b[3][2], b[3][3]); \
      mma16816(acc[0], W[k4], b[0][0], b[0][1]); mma16816(acc[1], W[(k4) + 1], b[0][2], b[0][3]); \
      mma16816(acc[2], W[k5], b[1][0], b[1][1]); mma16816(acc[3], W[(k5) + 1], b[1][2], b[1][3]); }
      if (warp == 1) PROF_T(27);
      mbar_wait(BAR(B_MEM + 0), par);
      if (warp == 0) PROF_T(0);
      if (warp == 1) PROF_T(24);
      KWAVE(0, 1, 0, 6, 12, 17, 22, 27)
      mbar_wait(BAR(B_MEM + 1), par);
      if (warp == 1) PROF_T(25);
      KWAVE(3072, 7, 2, 8, 14, 19, 24, 29)
      mbar_wait(BAR(B_MEM + 2), par);
      if (warp == 1) PROF_T(26);
      {
        uint32_t b[4][4];
        ldsm4t(ma + 6144, b[0]); ldsm4t(ma + 6656, b[1]); ldsm4t(ma + 7168, b[2]); ldsm4t(ma + 7680, b[3]);
        BB_FENCE(13);
        mma16816(acc[0], W[4], b[0][0], b[0][1]); mma16816(acc[1], W[5], b[0][2], b[0][3]);
        mma16816(acc[2], W[10], b[1][0], b[1][1]); mma16816(acc[3], W[11], b[1][2], b[1][3]);
        mma16816(acc[0], W[16], b[2][0], b[2][1]); mma16816(acc[1], W[21], b[2][2], b[2][3]);
        mma16816(acc[2], W[26], b[3][0], b[3][1]); mma16816(acc[3], W[31], b[3][2], b[3][3]);
      }
#undef KWAVE
      const uint32_t w0 = pack_bf16((acc[0][0] + acc[1][0]) + (acc[2][0] + acc[3][0]), (acc[0][1] + acc[1][1]) + (acc[2][1] + acc[3][1]));
      const uint32_t w1 = pack_bf16((acc[0][2] + acc[1][2]) + (acc[2][2] + acc[3][2]), (acc[0][3] + acc[1][3]) + (acc[2][3] + acc[3][3]));
      auto vsend = [&]() {
        const uint32_t vb = BAR(B_VM + r4), a_out = sb + SM_VM + hl * 2048 + (v0 - 2 * nqk + warp) * 256 + r4 * 4096 + (l16 >> 2);
#pragma unroll
        for (int d = 1; d < CLS; d++) {
          uint32_t t = rank + d; if (t >= CLS) t -= CLS;
          const uint32_t ra = mapa(a_out, t), rb = mapa(vb, t);
          st_async32(ra, w0, rb); st_async32(ra + 128, w1, rb);
        }
        sts32(a_out, w0); sts32(a_out + 128, w1);
        __syncwarp();
        mbar_arrive_tx_if(vb, warp == 7 ? 4096 - nv * 256 : 0, l16 == 0);
      };
      if (!isv) stsm2t(sb + SM_KX + 8192 + kring + warp * 256 + l16, w0, w1);
      uint32_t a_k = sb + SM_KX + nqk * 1024 + warp * 128 + kring + (l16 & 0x70) + ((l16 & 0x180) << 2);
      PIN(a_k);
      bar_arrive_if(2, 320, (warp >> 1) == 2);
      if (isv) vsend();
      auto ksend = [&]() {
        const uint32_t s3 = (uint32_t)s / 3u, own = hl * 3 + (s - s3 * 3), kp = s3 & 1;
        const uint32_t ra = mapa(sb + SM_KMA + kp * 2048 + (qk0 - nqk + warp) * 256 + (l16 >> 2), own), rb = mapa(BAR(B_KMF + kp), own);
        st_async32(ra, w0, rb); st_async32(ra + 128, w1, rb);
      };
      if (warp < 4) {
        bar_sync(2, 320);
        if (warp == 0) PROF_T(2);
        scores(sb + SM_KX + 8192 + kring + l16, a_k, 2048, warp, l16);
        if (!isq) ksend();
      } else if (!isv) {
        ksend();
      }
      if (warp == 0) PROF_T(3);
      kring = kring == 2 * KX_SLOT ? 0u : kring + KX_SLOT;
      if (warp < 4) {
       uint32_t pb[5];
       {
        uint32_t va[8][4], vm[2][4];
        if (s == 0) mbar_wait(BAR(B_VF), 0);
        const uint32_t a_v = sb + SM_V + warp * 4096 + r4 * 16384 + l16;
        ldsm4(a_v, va[0]); ldsm4(a_v + 1024, va[2]); ldsm4(a_v + 2048, va[4]);
        const uint32_t a_ss = sb + SM_SC + (warp >> 1) * 1920 + l16;
        uint32_t a_s3 = a_ss + (l16 >> 7) * 512 + 512;
        PIN(a_s3);
        mbar_wait(BAR(B_VM + r4), (s >> 2) & 1);
        ldsm4(sb + SM_VM + warp * 1024 + r4 * 4096 + l16, vm[0]);
        ldsm4(sb + SM_VM + warp * 1024 + 512 + r4 * 4096 + l16, vm[1]);
        if (warp == 0) PROF_T(13);
        mbar_wait(BAR(B_SC), par);
        if (warp == 0) PROF_T(4);
        __half2 sv[5];
        {
          uint32_t r0[4], r1[4], r2[4], r3[4];
          ldsm4(a_ss, r0); ldsm4(a_ss + 640, r1); ldsm4(a_ss + 1280, r2); ldsm4(a_s3, r3);
          BB_FENCE(15);
#define H2(x) (*reinterpret_cast<__half2*>(&(x)))
#pragma unroll
          for (int i = 0; i < 4; i++) sv[i] = __hadd2(__hadd2(H2(r0[i]), H2(r1[i])), H2(r2[i]));
          sv[4] = __hadd2(__hadd2(H2(r3[0]), H2(r3[1])), H2(r3[2]));
        }
        __half2 mx = __hmax2(__hmax2(__hmax2(sv[0], sv[1]), __hmax2(sv[2], sv[3])), sv[4]);
        mx = __hmax2(mx, __lowhigh2highlow(mx));
        {
          const __half2 m1 = __shfl_xor_sync(0xffffffffu, mx, 1), m2 = __shfl_xor_sync(0xffffffffu, mx, 2), m3 = __shfl_xor_sync(0xffffffffu, mx, 3);
          ldsm4(a_v + 3072, va[6]); ldsm4(a_v + 512, va[1]);
          BB_FENCE(17);
          mx = __hmax2(__hmax2(mx, m1), __hmax2(m2, m3));
        }
#define PEXP(i) { const float2 d = __half22float2(__hsub2(sv[i], mx)); pb[i] = pack_bf16(ex2(d.x), ex2(d.y)); }
        PEXP(4) PEXP(0) PEXP(1) PEXP(2) PEXP(3)
#undef PEXP
#undef H2
        float o[5][4];
#pragma unroll
        for (int i = 0; i < 5; i++) { o[i][0] = o[i][1] = o[i][2] = o[i][3] = 0.f; }
        mma1688(o[0], vm[0][0], vm[0][1], pb[4]); mma1688(o[1], vm[0][2], vm[0][3], pb[4]);
        mma1688(o[2], vm[1][0], vm[1][1], pb[4]); mma1688(o[3], vm[1][2], vm[1][3], pb[4]);
        mma16816(o[0], va[0], pb[0], pb[1]); mma16816(o[1], va[2], pb[0], pb[1]);
        BB_FENCE(19);
        if (warp == 0) PROF_T(1);
        ldsm4(a_v + 1536, va[3]); ldsm4(a_v + 2560, va[5]);
        mma16816(o[2], va[4], pb[0], pb[1]); mma16816(o[3], va[6], pb[0], pb[1]);
        BB_FENCE(21);
        ldsm4(a_v + 3584, va[7]);
        mma16816(o[0], va[1], pb[2], pb[3]); mma16816(o[1], va[3], pb[2], pb[3]);
        mma16816(o[2], va[5], pb[2], pb[3]); mma16816(o[4], va[7], pb[2], pb[3]);
        stsm4(sb + SM_O + warp * 1024 + l16, pack_bf16(o[0][0], o[0][1]), pack_bf16(o[0][2], o[0][3]), pack_bf16(o[1][0], o[1][1]), pack_bf16(o[1][2], o[1][3]));
        stsm4(sb + SM_O + warp * 1024 + 512 + l16, pack_bf16(o[2][0], o[2][1]), pack_bf16(o[2][2], o[2][3]),
              pack_bf16(o[3][0] + o[4][0], o[3][1] + o[4][1]), pack_bf16(o[3][2] + o[4][2], o[3][3] + o[4][3]));
       }
       if (s == NSEG - 1) break;
       bar_arrive(3, 256);
       if (warp == 0) PROF_T(5);
       if ((warp & 1) == 0) {
        float l = ((bf_lo(pb[0]) + bf_hi(pb[0])) + (bf_lo(pb[1]) + bf_hi(pb[1]))) + ((bf_lo(pb[2]) + bf_hi(pb[2])) + (bf_lo(pb[3]) + bf_hi(pb[3])));
        l += bf_lo(pb[4]) + bf_hi(pb[4]);
        l += __shfl_xor_sync(0xffffffffu, l, 1);
        l += __shfl_xor_sync(0xffffffffu, l, 2);
        if ((l16 & 0x30) == 0) sts32(sb + SM_LI + (warp >> 1) * 128 + (l16 >> 4), __float_as_uint(rcp(l)));
        bar_arrive(8, 192);
       }
      }
      if (g < NSEG) { mbar_wait(BAR(B_XAF), par ^ 1); if (warp < 4 || NE1 > 16) mbar_wait(BAR(B_XNF), par ^ 1); }
      bar_sync(warp < 4 ? 7 : 9, warp < 4 ? 384 : 288);
      if (s == NSEG - 1) break;
      if (warp == 4) PROF_T(7);
     } else {
      mbar_wait(BAR(g ? B_XN1 : B_XAF), 0);
      mbar_wait(BAR(g ? B_XN1 : B_XNF), 0);
     }
     {
      float c[16];
      uint32_t dlo = ((((sb + SM_XN) & 0x3FFFF) >> 4) | (1u << 16)) + (g == 1 ? (SM_V + 32768 - SM_XN) >> 4 : 0);
      asm volatile("" : "+r"(dlo));
      wg_fence();
#pragma unroll
      for (int ks = 0; ks < 32; ks++) {
        if (ks == NE1) bar_sync_if(7, 384, warp >= 4 && s >= 0);
        wgmma_rs_n32(c, W[ks], ((uint64_t)0x40000040u << 32) | (uint64_t)(dlo + (ks >> 2) * 256 + (ks & 3) * 2), ks);
        if (ks == 15) wg_commit();
      }
      wg_commit();
      const uint32_t d = sb + SM_KX + gring + warp * 1024 + l16;
      gring = gring == 2 * KX_SLOT ? 0u : gring + KX_SLOT;
      const bool rel = l16 == 0 && (warp & 3) == 0 && g != 1 && g < NSEG;
      wg_wait<1>();
      if (rel) mbar_arrive_remote(x_e + 8 * (B_XAE - B_XNE));
      if (g > 0) mbar_wait(BAR(B_STE), (g - 1) & 1);
      if (s >= 0) mbar_wait(BAR(B_VF + ((s + 1) & 3)), ((s + 1) >> 2) & 1);
      wg_wait<0>();
      if (warp == 0) PROF_T(14);
      if (warp == 4) PROF_T(12);
      if (rel) mbar_arrive_remote(x_e);
      uint32_t r[8];
#pragma unroll
      for (int nt = 0; nt < 4; nt++) { r[nt] = pack_bf16(c[4 * nt], c[4 * nt + 1]); r[4 + nt] = pack_bf16(c[4 * nt + 2], c[4 * nt + 3]); }
      if (g < NSEG) {
        if (isv) {
          stsm4(d, r[0], r[4], r[1], r[5]); stsm4(d + 512, r[2], r[6], r[3], r[7]);
        } else {
          stsm4t(d, r[0], r[1], r[2], r[3]); stsm4t(d + 512, r[4], r[5], r[6], r[7]);
        }
        __syncwarp();
        if (l16 == 0) mbar_arrive(BAR(B_STF));
      }
     }
     if (warp == 0 && s >= 0) PROF_T(6);
     if (warp == 4 && s >= 0) PROF_T(15);
    }
    if (tid == 0) GT(blockIdx.x, 3);
    cluster_sync();
    if (tid == 0) GT(blockIdx.x, 4);
  } else if (warp < 12) {
    reg_dec<112>();
    const int a = warp - 8;
    const uint32_t wo = sb + SM_WO + a * 12288;
    uint32_t R[16][4];
    {
      uint32_t F[8][4];
      const int kr = (lane & 7) + ((lane >> 4) << 3), ch = (lane >> 3) & 1;
      const uint32_t aS = sb + SM_WO + 32768 + (a & 1) * 8192 + kr * 64 + ((((a >> 1) * 2 + ch) ^ ((kr >> 1) & 3)) << 4);
      const uint32_t aF = sb + SM_WO + kr * 128 + (((a + 4 * ch) ^ (kr & 7)) << 4);
      const uint32_t aF0 = aF + (a & 1) * 16384, aF1 = aF + ((a & 1) ^ 1) * 16384;
      cluster_wait(); cluster_arrive_rlx();
      mbar_wait(BAR(B_WO), 0);
      if (tid == 256) GT(blockIdx.x + 104, 76);
#pragma unroll
      for (int u = 0; u < 4; u++) { ldsm4t(aS + (4 + u) * 1024, R[u]); ldsm4t(aF0 + (4 + u) * 2048, R[4 + u]); }
#pragma unroll
      for (int u = 0; u < 8; u++) ldsm4t(aF1 + u * 2048, R[8 + u]);
#pragma unroll
      for (int u = 0; u < 4; u++) { ldsm4t(aS + u * 1024, F[u]); ldsm4t(aF0 + u * 2048, F[4 + u]); }
      bar_sync(4, 128);
#pragma unroll
      for (int u = 0; u < 8; u++) sts128(wo + u * 512 + lane * 16, F[u][0], F[u][1], F[u][2], F[u][3]);
      __syncwarp();
    }
    if (lane < CLS) mbar_arrive_remote(mapa(BAR(B_P3), lane));
    cluster_wait();
    sts128(sb + SM_WX + a * 512 + lane * 16, R[15][0], R[15][1], R[15][2], R[15][3]);
    mbar_wait(BAR(B_P3), 0);
    if (tid == 256) GT(blockIdx.x, 5);
    uint32_t l16 = (uint32_t)__shfl_sync(0xffffffffu, lane * 16, lane);

    const int zu = cl;
    constexpr int ZK = 0x1000000;
    const uint32_t u_mem = sb + SM_MEM + (rank * 4 + a) * 128;
    const uint32_t w2off = 6144 + (rank < 2 ? 0 : (4 - 2 * (int)rank) * 128);
    auto send_unit = [&](int wv, uint32_t val) {
      const uint32_t lm = u_mem + (wv < 2 ? wv * 3072 : w2off) + (l16 >> 2);
#pragma unroll
      for (int d = 1; d < CLS; d++) {
        uint32_t t = rank + d; if (t >= CLS) t -= CLS;
        st_async32(mapa(lm, t), val, mapa(BAR(B_MEM + wv), t));
      }
      sts32(lm, val);
      __syncwarp();
      mbar_arrive_tx_if(BAR(B_MEM + wv), a == 0 ? (wv < 2 ? 5 * 512 : (16 - (nu - 8)) * 128) : 0, l16 == 0);
    };
    const bool has3 = a + 8 < nu;
    {
      const unsigned short* m0 = reinterpret_cast<const unsigned short*>(mem0);
#pragma unroll
      for (int wv = 0; wv < 3; wv++) {
        if (wv < 2 || has3) {
          const int col = (cb + a + 4 * wv) * 8 + (lane >> 2), r = (lane & 3) * 2;
          uint32_t val = (uint32_t)m0[r * DM + col] | ((uint32_t)m0[(r + 1) * DM + col] << 16);
          send_unit(wv, val);
        }
      }
    }
    poll_ge(&g_lncnt, lds32(sb + SM_EP) * NHELP);
    unsigned char* const exu = g_ex + rank * EX_RANK + a * EX_WARP;
    const uint32_t u_o0 = sb + SM_O + (a & 1) * 2048, u_o1 = sb + SM_O + ((a & 1) ^ 1) * 2048;

#pragma unroll 1
    for (int s = 0;; s++) {
      PIN(l16);
      uint32_t T[8][4];
      const uint32_t u_q = sb + SM_KX + 8192 + ((uint32_t)s % 3u) * KX_SLOT;
      bar_sync(2, 320);
      if (a == 0) scores(u_q + l16, u_q + nqk * 256 + l16, 512, 4, l16);
      if (s == NSEG - 1) break;
#pragma unroll
      for (int u = 0; u < 8; u++) lds128(wo + u * 512 + l16, T[u]);
      bar_sync(3, 256);
      if (a == 0) PROF_T(8);
      float hf[4] = {0.f, 0.f, 0.f, 0.f}, hg[4] = {0.f, 0.f, 0.f, 0.f}, f0[4] = {0.f, 0.f, 0.f, 0.f}, f1[4] = {0.f, 0.f, 0.f, 0.f};
      float f2[4] = {0.f, 0.f, 0.f, 0.f}, f3[4] = {0.f, 0.f, 0.f, 0.f}, f4[4] = {0.f, 0.f, 0.f, 0.f}, f5[4] = {0.f, 0.f, 0.f, 0.f};
      float k0, k1;
      {
        uint32_t b0[4], b1[4], b2[4], b3[4], c0[4], c1[4], c2[4], c3[4];
        ldsm4t(u_o0 + l16, b0); ldsm4t(u_o0 + 512 + l16, b1);
        BB_FENCE(1);
        mma16816(hf, T[0], b0[0], b0[1]); mma16816(hg, T[1], b0[2], b0[3]);
        mma16816(f0, T[4], b0[0], b0[1]); mma16816(f1, T[5], b0[2], b0[3]);
        ldsm4t(u_o0 + 1024 + l16, b2);
        AFENCE(3);
        mma16816(hf, T[2], b1[0], b1[1]); mma16816(hg, T[3], b1[2], b1[3]);
        ldsm4t(u_o0 + 1536 + l16, b3); ldsm4t(u_o1 + l16, c0);
        AFENCE(5);
        mma16816(f0, T[6], b1[0], b1[1]); mma16816(f1, T[7], b1[2], b1[3]);
        ldsm4t(u_o1 + 512 + l16, c1); ldsm4t(u_o1 + 1024 + l16, c2); ldsm4t(u_o1 + 1536 + l16, c3);
        lds128(sb + SM_WX + a * 512 + l16, T[0]);
        AFENCE(7);
        mma16816(hf, R[0], b2[0], b2[1]); mma16816(hg, R[1], b2[2], b2[3]);
        mma16816(f0, R[4], b2[0], b2[1]); mma16816(f1, R[5], b2[2], b2[3]);
        mma16816(hf, R[2], b3[0], b3[1]); mma16816(hg, R[3], b3[2], b3[3]);
        mma16816(f2, R[8], c0[0], c0[1]); mma16816(f3, R[9], c0[2], c0[3]);
        mma16816(f0, R[6], b3[0], b3[1]); mma16816(f1, R[7], b3[2], b3[3]);
        mma16816(f4, R[10], c1[0], c1[1]);
        {
          const float x0 = (a & 1) ? hf[0] + hg[0] : hf[2] + hg[2], x1 = (a & 1) ? hf[1] + hg[1] : hf[3] + hg[3];
          k0 = (a & 1) ? hf[2] + hg[2] : hf[0] + hg[0]; k1 = (a & 1) ? hf[3] + hg[3] : hf[1] + hg[1];
          asm volatile("st.shared.v2.f32 [%0], {%1,%2};" ::"r"(sb + SM_PAIR + (a ^ 1) * 256 + (l16 >> 1)), "f"(x0), "f"(x1) : "memory");
        }
        AFENCE(9);
        mma16816(f5, R[11], c1[2], c1[3]);
        mma16816(f2, R[12], c2[0], c2[1]); mma16816(f3, R[13], c2[2], c2[3]);
        mma16816(f4, R[14], c3[0], c3[1]); mma16816(f5, T[0], c3[2], c3[3]);
      }
      bar_sync(8, 192);
      float y0, y1, i0, i1, j0, j1;
      asm volatile("ld.volatile.shared.v2.f32 {%0,%1}, [%2];" : "=f"(i0), "=f"(i1) : "r"(sb + SM_LI + (a & 1) * 128 + ((l16 >> 1) & 24)) : "memory");
      asm volatile("ld.volatile.shared.v2.f32 {%0,%1}, [%2];" : "=f"(j0), "=f"(j1) : "r"(sb + SM_LI + ((a & 1) ^ 1) * 128 + ((l16 >> 1) & 24)) : "memory");
      asm volatile("ld.volatile.shared.v2.f32 {%0,%1}, [%2];" : "=f"(y0), "=f"(y1) : "r"(sb + SM_PAIR + a * 256 + (l16 >> 1)) : "memory");
      unsigned char* wp = exu + (s & 3) * EX_BUF + l16;
      BB_FENCE(11);
      {
        const uint32_t e2 = pack_f16(fmaf(y0, j0, k0 * i0), fmaf(y1, j1, k1 * i1));
        const float s0 = (f0[0] + f1[0]) * i0, s1 = (f0[1] + f1[1]) * i1, s2 = (f0[2] + f1[2]) * i0, s3 = (f0[3] + f1[3]) * i1;
        const uint32_t e0 = pack_f16(fmaf((f2[0] + f3[0]) + (f4[0] + f5[0]), j0, s0), fmaf((f2[1] + f3[1]) + (f4[1] + f5[1]), j1, s1));
        const uint32_t e1 = pack_f16(fmaf((f2[2] + f3[2]) + (f4[2] + f5[2]), j0, s2), fmaf((f2[3] + f3[3]) + (f4[3] + f5[3]), j1, s3));
        asm volatile("red.relaxed.gpu.global.add.noftz.v4.f16x2 [%0], {%1,%2,%3,%4};"
                     ::"l"(wp), "r"(e0), "r"(e1), "r"(e2), "r"(0x3c00u) : "memory");
      }
      bar_arrive(7, 384);
      const uint32_t tw = clk32();
      if (a == 0) PROF_T(9);
      PROF_T(28 + a);
      if ((int)(l16 >> 5) == cl)
        asm volatile("st.relaxed.gpu.global.v4.b32 [%0], {%1,%1,%1,%1};" ::"l"(exu + ((s + 2) & 3) * EX_BUF + l16), "r"(0u) : "memory");
      uint32_t v[4];
      int it = 0;
      const uint32_t scr = sb + SM_SCR + a * 1024 + (uint32_t)__shfl_xor_sync(0xffffffffu, l16, 0);
#define POLL() asm volatile("ld.relaxed.gpu.global.v4.b32 {%0,%1,%2,%3}, [%4];" : "=r"(v[0]), "=r"(v[1]), "=r"(v[2]), "=r"(v[3]) : "l"(wp) : "memory")
#define POK() __all_sync(0xffffffffu, v[3] == 0x4c00u)
      while (clk32() - tw < POLL_DELAY) {}
      POLL();
      while (clk32() - tw < POLL_DELAY + POLL_GAP) {}
      cp_async16(scr, wp);
      asm volatile("cp.async.commit_group;" ::: "memory");
      while (clk32() - tw < POLL_DELAY + 2 * POLL_GAP) {}
      cp_async16(scr + 512, wp);
      asm volatile("cp.async.commit_group;" ::: "memory");
      BB_FENCE(13);
      if (!POK()) {
        it = 1;
        asm volatile("cp.async.wait_group 1;" ::: "memory");
        lds128(scr, v);
        if (!POK()) {
          it = 2;
          asm volatile("cp.async.wait_group 0;" ::: "memory");
          lds128(scr + 512, v);
          while (!POK()) {
            if (++it > 20000) { *(volatile unsigned int*)&g_err = 2; break; }
            POLL();
          }
        }
      }
#undef POLL
#undef POK
      if (a == 0) PROF_T(10);
      PROF_T(16 + a);
      send_unit(0, f16_to_bf16(v[0]));
      send_unit(1, f16_to_bf16(v[1]));
      if (has3) send_unit(2, f16_to_bf16(v[2]));
    }
    cp_async_wait_all();
    __syncwarp();
    cluster_sync();
  } else {
    reg_dec<48>();
    if (tid == 480) {
#pragma unroll 1
      for (int i = WL_AHEAD; i < 8; i++) { mbar_wait(BAR(B_WL + i - WL_AHEAD), 0); wload(i); }
      mbar_arrive_tx(BAR(B_WO), 49152);
#pragma unroll 1
      for (int i = 0; i < 4; i++) {
        mbar_wait(BAR(B_WL + min(7, 8 - WL_AHEAD + i)), 0);
        tma2d(sb + SM_WO + i * 8192, &wm.o64, cb * 8, cl * 256 + i * 64, BAR(B_WO));
        tma2d(sb + SM_WO + 32768 + i * 4096, &wm.o32, cb * 8 + 64, cl * 256 + i * 64, BAR(B_WO));
      }
    }
    __syncwarp();
    cluster_wait(); cluster_arrive_rlx();
    if (tid == 384) {
      mbar_arrive_tx(BAR(B_XAF), 16384);
      mbar_arrive_tx(BAR(B_XNF), 16384);
      mbar_arrive_tx(BAR(B_XN1), 32768);
      if (rank == 0) {
        poll_ge(&g_ln0, lds32(sb + SM_EP) * 64);
        fence_async_all();
#pragma unroll 1
        for (int kc = 0; kc < 8; kc++)
          bulk_g2s_mc(sb + SM_XN + kc * 4096, g_xn + (size_t)kc * S_TOK * 128, 4096, BAR(kc < 4 ? B_XAF : B_XNF), 0x3f);
      }
    }
    __syncwarp();
    cluster_wait();
    if (tid == 384 && rank == 0) {
#pragma unroll 1
      for (int kc = 0; kc < 8; kc++)
        bulk_g2s_mc(sb + SM_V + 32768 + kc * 4096, g_xn + ((size_t)kc * S_TOK + 32) * 128, 4096, BAR(B_XN1), 0x3f);
    }
    if (warp == 15) {
      if (lane == 0) {
        if (rank == 0) {
          poll_ge(&g_lncnt, lds32(sb + SM_EP) * NHELP);
          fence_async_all();
        }
        for (int h = 4; h < 2 * NSEG; h++) {
          const int g = h >> 1;
          const uint32_t bf = BAR(h & 1 ? B_XNF : B_XAF);
          mbar_wait(bf, g & 1);
          mbar_arrive_tx(bf, 16384);
          if (rank == 0) {
            mbar_wait(BAR(h & 1 ? B_XNE : B_XAE), g & 1);
#pragma unroll 1
            for (int kc = (h & 1) * 4; kc < (h & 1) * 4 + 4; kc++)
              bulk_g2s_mc(sb + SM_XN + kc * 4096, g_xn + ((size_t)kc * S_TOK + g * 32) * 128, 4096, bf, 0x3f);
          }
        }
      }
    } else if (warp == 12) {
      if (lane == 0) {
        for (int g = 0; g < NSEG; g++) {
          const int slot = g & 3, slot8 = g & 7;
          mbar_arrive_tx(BAR(B_VF + (g % NVST)), 16384);
          mbar_wait(BAR(B_STF), g & 1);
          if (g >= 2) mbar_hint(BAR(B_MEM + H2W), (g - 1) & 1);
          fence_async_smem();
          unsigned char* vdst = g_v + (size_t)(slot * NCL + cl) * 16384 + (hl * 16 + v0 * 2) * 512;
          const uint32_t src = sb + SM_KX + (g % 3) * KX_SLOT;
          bulk_s2g(vdst, src + 2 * nqk * 1024, nv * 1024);
          bulk_s2g(g_q + (size_t)(slot8 * NH + head) * 8192 + qk0 * 1024, src, nqk * 1024);
          bulk_s2g(g_k + (size_t)(slot8 * NH + head) * 8192 + qk0 * 1024, src + nqk * 1024, nqk * 1024);
          bulk_commit();
          bulk_wait_read();
          mbar_arrive(BAR(B_STE));
          bulk_wait_all();
          fence_async_all();
          if (g >= NVST) mbar_wait(BAR(B_VE + (g % NVST)), ((g / NVST) - 1) & 1);
          if (g >= 2) mbar_hint(BAR(B_SC), (g - 1) & 1);
          bulk_g2s_mc(sb + SM_V + (g % NVST) * 16384 + (hl * 16 + v0 * 2) * 512, vdst, nv * 1024, BAR(B_VF + (g % NVST)), 0x3f);
          mbar_arrive_remote_rel(mapa(BAR(B_QKR + ((g / 3) & 1)), hl * 3 + (g % 3)));
        }
      }
    } else {
      const int rt = warp - 13;
      int n = 0;
      if (rt == 0 && lane == 0) mbar_arrive_tx(BAR(B_KMF), 2048);
      for (int g = jj; g < NSEG; g += 3, n++) {
        if (rt == 0 && lane == 0) {
          if (g + 3 < NSEG) mbar_arrive_tx(BAR(B_KMF + ((n + 1) & 1)), 2048);
          mbar_wait_acq(BAR(B_QKR + (n & 1)), (n >> 1) & 1);
          fence_async_all();
          mbar_arrive_tx(BAR(B_ATF), 16384);
          bulk_g2s(sb + SM_ATQ, g_q + (size_t)((g & 7) * NH + head) * 8192, 8192, BAR(B_ATF));
          bulk_g2s(sb + SM_ATK, g_k + (size_t)((g & 7) * NH + head) * 8192, 8192, BAR(B_ATF));
        }
        __syncwarp();
#define GA(i) if (rt == 1 && lane == 0 && g >= 61) GT(blockIdx.x, 72 + (i))
        GA(0);
        mbar_wait(BAR(B_ATF), n & 1);
        GA(1);
        mbar_wait(BAR(B_KMF + (n & 1)), (n >> 1) & 1);
        GA(2);
        float sc[5][4];
#pragma unroll
        for (int t = 0; t < 5; t++) sc[t][0] = sc[t][1] = sc[t][2] = sc[t][3] = 0.f;
        {
          const uint32_t qa = sb + SM_ATQ + (lane >> 4) * 512 + (2 * rt + ((lane >> 3) & 1)) * 128 + (lane & 7) * 16;
          const uint32_t ka = sb + SM_ATK + lane * 16;
          const uint32_t kma = sb + SM_KMA + (n & 1) * 2048 + (lane & 15) * 16;
#pragma unroll 1
          for (int ks = 0; ks < 8; ks++) {
            uint32_t q[4], b0[4], b1[4], bm[2];
            ldsm4(qa + ks * 1024, q);
            ldsm4(ka + ks * 1024, b0); ldsm4(ka + ks * 1024 + 512, b1);
            ldsm2t(kma + ks * 256, bm);
            mma16816(sc[0], q, b0[0], b1[0]);
            mma16816(sc[1], q, b0[1], b1[1]);
            if (rt) { mma16816(sc[2], q, b0[2], b1[2]); mma16816(sc[3], q, b0[3], b1[3]); }
            mma16816(sc[4], q, bm[0], bm[1]);
          }
        }
        GA(3);
        const int r0 = 16 * rt + (lane >> 2), kq = (lane & 3) * 2;
        float m0 = fmaxf(sc[4][0], sc[4][1]), m1 = fmaxf(sc[4][2], sc[4][3]);
#pragma unroll
        for (int t = 0; t < 4; t++) {
          const int k0 = 8 * t + kq;
          if (k0 > r0) sc[t][0] = -INFINITY;
          if (k0 + 1 > r0) sc[t][1] = -INFINITY;
          if (k0 > r0 + 8) sc[t][2] = -INFINITY;
          if (k0 + 1 > r0 + 8) sc[t][3] = -INFINITY;
          m0 = fmaxf(m0, fmaxf(sc[t][0], sc[t][1]));
          m1 = fmaxf(m1, fmaxf(sc[t][2], sc[t][3]));
        }
        m0 = fmaxf(m0, __shfl_xor_sync(0xffffffffu, m0, 1)); m0 = fmaxf(m0, __shfl_xor_sync(0xffffffffu, m0, 2));
        m1 = fmaxf(m1, __shfl_xor_sync(0xffffffffu, m1, 1)); m1 = fmaxf(m1, __shfl_xor_sync(0xffffffffu, m1, 2));
        const float n0 = -m0 * SC_LOG2E, n1 = -m1 * SC_LOG2E;
        uint32_t p[5][2];
        float l0 = 0.f, l1 = 0.f;
#pragma unroll
        for (int t = 0; t < 5; t++) {
          p[t][0] = pack_bf16(ex2(fmaf(sc[t][0], SC_LOG2E, n0)), ex2(fmaf(sc[t][1], SC_LOG2E, n0)));
          p[t][1] = pack_bf16(ex2(fmaf(sc[t][2], SC_LOG2E, n1)), ex2(fmaf(sc[t][3], SC_LOG2E, n1)));
          l0 += bf_lo(p[t][0]) + bf_hi(p[t][0]);
          l1 += bf_lo(p[t][1]) + bf_hi(p[t][1]);
        }
        l0 += __shfl_xor_sync(0xffffffffu, l0, 1); l0 += __shfl_xor_sync(0xffffffffu, l0, 2);
        l1 += __shfl_xor_sync(0xffffffffu, l1, 1); l1 += __shfl_xor_sync(0xffffffffu, l1, 2);
        const float i0 = 1.f / l0, i1 = 1.f / l1;
        GA(4);
        mbar_wait(BAR(B_VF + (g % NVST)), (g / NVST) & 1);
        mbar_wait(BAR(B_VM + (g & 3)), (g >> 2) & 1);
        if (n > 0) { if (lane == 0) bulk_wait_read(); __syncwarp(); }
        GA(5);
        {
          const uint32_t va = sb + SM_V + (g % NVST) * 16384 + hl * 8192 + lane * 16;
          const uint32_t vma = sb + SM_VM + (g & 3) * 4096 + hl * 2048 + (lane & 15) * 16;
          const int row = (lane & 7) + ((lane >> 3) & 1) * 8;
          const uint32_t oxb = sb + SM_OX + rt * 4096 + row * 128;
#pragma unroll 1
          for (int np = 0; np < 8; np++) {
            uint32_t x0[4], x1[4], xm[2];
            ldsm4(va + np * 1024, x0);
            if (rt) ldsm4(va + np * 1024 + 512, x1);
            ldsm2(vma + np * 256, xm);
            float o0[4] = {0.f, 0.f, 0.f, 0.f}, o1[4] = {0.f, 0.f, 0.f, 0.f};
            mma16816r(o0, p[0][0], p[0][1], p[1][0], p[1][1], x0[0], x0[2]);
            mma16816r(o1, p[0][0], p[0][1], p[1][0], p[1][1], x0[1], x0[3]);
            if (rt) {
              mma16816r(o0, p[2][0], p[2][1], p[3][0], p[3][1], x1[0], x1[2]);
              mma16816r(o1, p[2][0], p[2][1], p[3][0], p[3][1], x1[1], x1[3]);
            }
            mma1688(o0, p[4][0], p[4][1], xm[0]);
            mma1688(o1, p[4][0], p[4][1], xm[1]);
            const int c16 = (2 * np + (lane >> 4));
            stsm4(oxb + (c16 >> 3) * 2048 + (((c16 & 7) ^ (row & 7)) << 4),
                  pack_bf16(o0[0] * i0, o0[1] * i0), pack_bf16(o0[2] * i1, o0[3] * i1),
                  pack_bf16(o1[0] * i0, o1[1] * i0), pack_bf16(o1[2] * i1, o1[3] * i1));
          }
        }
        GA(6);
        fence_async_smem();
        __syncwarp();
        if (lane < CLS) mbar_arrive_remote(mapa(BAR(B_VE + (g % NVST)), lane));
        if (lane == 0) {
          unsigned char* dst = g_ox + ((size_t)(head * 2) * S_TOK + g * 32 + rt * 16) * 128;
          bulk_s2g(dst, sb + SM_OX + rt * 4096, 2048);
          bulk_s2g(dst + (size_t)S_TOK * 128, sb + SM_OX + rt * 4096 + 2048, 2048);
          bulk_commit();
          bulk_wait_all();
          GA(7);
          fence_async_all();
          asm volatile("red.release.gpu.global.add.u32 [%0], 1;" ::"l"(&g_cnt[(head >> 2) * NSEG + g]) : "memory");
          if (rt == 1 && g >= 61) GT(blockIdx.x, 6);
        }
        bar_sync(6, 64);
      }
    }
    __syncwarp();
    cluster_sync();
  }
}

#define HELP_DELAY 3000
constexpr int G_STAGES = 4, G_STAGE_BYTES = 49152;
constexpr int G_SM_HST = G_STAGES * G_STAGE_BYTES;
constexpr int G_SM_BAR = G_SM_HST + 32768;
constexpr int G_SM_FIN = G_SM_BAR + 512;
constexpr int G_SM_END = G_SM_FIN + 1024;
constexpr int G_SM_RING = 131072;
static_assert(G_SM_RING + 3 * 32768 <= G_SM_BAR && G_SM_END <= 232448, "smem");
__device__ __forceinline__ void wgmma_ss_n256(float* c, uint64_t da, uint64_t db, int acc) {
  asm volatile("{\n.reg .pred p;\nsetp.ne.b32 p, %130, 0;\n"
    "wgmma.mma_async.sync.aligned.m64n256k16.f32.bf16.bf16 {"
    "%0,%1,%2,%3,%4,%5,%6,%7,%8,%9,%10,%11,%12,%13,%14,%15,%16,%17,%18,%19,%20,%21,%22,%23,%24,%25,%26,%27,%28,%29,%30,%31,"
    "%32,%33,%34,%35,%36,%37,%38,%39,%40,%41,%42,%43,%44,%45,%46,%47,%48,%49,%50,%51,%52,%53,%54,%55,%56,%57,%58,%59,%60,%61,%62,%63,"
    "%64,%65,%66,%67,%68,%69,%70,%71,%72,%73,%74,%75,%76,%77,%78,%79,%80,%81,%82,%83,%84,%85,%86,%87,%88,%89,%90,%91,%92,%93,%94,%95,"
    "%96,%97,%98,%99,%100,%101,%102,%103,%104,%105,%106,%107,%108,%109,%110,%111,%112,%113,%114,%115,%116,%117,%118,%119,%120,%121,%122,%123,%124,%125,%126,%127"
    "}, %128, %129, p, 1, 1, 0, 1;\n}"
    : "+f"(c[0]), "+f"(c[1]), "+f"(c[2]), "+f"(c[3]), "+f"(c[4]), "+f"(c[5]), "+f"(c[6]), "+f"(c[7]),
      "+f"(c[8]), "+f"(c[9]), "+f"(c[10]), "+f"(c[11]), "+f"(c[12]), "+f"(c[13]), "+f"(c[14]), "+f"(c[15]),
      "+f"(c[16]), "+f"(c[17]), "+f"(c[18]), "+f"(c[19]), "+f"(c[20]), "+f"(c[21]), "+f"(c[22]), "+f"(c[23]),
      "+f"(c[24]), "+f"(c[25]), "+f"(c[26]), "+f"(c[27]), "+f"(c[28]), "+f"(c[29]), "+f"(c[30]), "+f"(c[31]),
      "+f"(c[32]), "+f"(c[33]), "+f"(c[34]), "+f"(c[35]), "+f"(c[36]), "+f"(c[37]), "+f"(c[38]), "+f"(c[39]),
      "+f"(c[40]), "+f"(c[41]), "+f"(c[42]), "+f"(c[43]), "+f"(c[44]), "+f"(c[45]), "+f"(c[46]), "+f"(c[47]),
      "+f"(c[48]), "+f"(c[49]), "+f"(c[50]), "+f"(c[51]), "+f"(c[52]), "+f"(c[53]), "+f"(c[54]), "+f"(c[55]),
      "+f"(c[56]), "+f"(c[57]), "+f"(c[58]), "+f"(c[59]), "+f"(c[60]), "+f"(c[61]), "+f"(c[62]), "+f"(c[63]),
      "+f"(c[64]), "+f"(c[65]), "+f"(c[66]), "+f"(c[67]), "+f"(c[68]), "+f"(c[69]), "+f"(c[70]), "+f"(c[71]),
      "+f"(c[72]), "+f"(c[73]), "+f"(c[74]), "+f"(c[75]), "+f"(c[76]), "+f"(c[77]), "+f"(c[78]), "+f"(c[79]),
      "+f"(c[80]), "+f"(c[81]), "+f"(c[82]), "+f"(c[83]), "+f"(c[84]), "+f"(c[85]), "+f"(c[86]), "+f"(c[87]),
      "+f"(c[88]), "+f"(c[89]), "+f"(c[90]), "+f"(c[91]), "+f"(c[92]), "+f"(c[93]), "+f"(c[94]), "+f"(c[95]),
      "+f"(c[96]), "+f"(c[97]), "+f"(c[98]), "+f"(c[99]), "+f"(c[100]), "+f"(c[101]), "+f"(c[102]), "+f"(c[103]),
      "+f"(c[104]), "+f"(c[105]), "+f"(c[106]), "+f"(c[107]), "+f"(c[108]), "+f"(c[109]), "+f"(c[110]), "+f"(c[111]),
      "+f"(c[112]), "+f"(c[113]), "+f"(c[114]), "+f"(c[115]), "+f"(c[116]), "+f"(c[117]), "+f"(c[118]), "+f"(c[119]),
      "+f"(c[120]), "+f"(c[121]), "+f"(c[122]), "+f"(c[123]), "+f"(c[124]), "+f"(c[125]), "+f"(c[126]), "+f"(c[127])
    : "l"(da), "l"(db), "r"(acc));
}

__global__ void __launch_bounds__(384, 1)
k_help(const __grid_constant__ CUtensorMap tmG, const __grid_constant__ CUtensorMap tmU, const __grid_constant__ CUtensorMap tmD,
       const __grid_constant__ CUtensorMap tmO, const __nv_bfloat16* __restrict__ x, __nv_bfloat16* __restrict__ out) {
  extern __shared__ __align__(1024) unsigned char smem[];
  const uint32_t sb = smem_u32(smem);
  const int tid = threadIdx.x, lane = tid & 31, warp = tid >> 5;
  const int j = blockIdx.x, ks8 = j >> 2, cg = j & 3;
  const uint32_t fullb = sb + G_SM_BAR, emptyb = fullb + 8 * G_STAGES, wbar = emptyb + 8 * G_STAGES;
  const uint32_t full2 = wbar + 8, empty2 = full2 + 8 * 12, done2 = empty2 + 8 * 3;
  if (tid == 0) GT(100 + j, 0);
  {
    uint4 v[5][2];
#pragma unroll
    for (int i = 0; i < 5; i++) {
      const int row = i * (NHELP * 12) + j * 12 + warp;
      if (row < S_TOK) {
        const uint4* src = reinterpret_cast<const uint4*>(x + (size_t)row * DM);
        v[i][0] = src[lane]; v[i][1] = src[lane + 32];
      }
    }
    if (tid == 32) sts32(done2 + 8, atomicAdd(&g_done, 1u) / NCTA + 1);
    if (j * 384 + tid < 4 * EX_BUF / 16) reinterpret_cast<uint4*>(g_ex)[j * 384 + tid] = make_uint4(0u, 0u, 0u, 0u);
#pragma unroll
    for (int i = 0; i < 5; i++) {
      const int row = i * (NHELP * 12) + j * 12 + warp;
      if (row < S_TOK) {
        ln_row(v[i][0], v[i][1]);
        unsigned char* d = g_xn + ((size_t)(lane >> 3) * S_TOK + row) * 128 + (((lane & 7) ^ (row & 7)) << 4);
        *reinterpret_cast<uint4*>(d) = v[i][0];
        *reinterpret_cast<uint4*>(d + (size_t)4 * S_TOK * 128) = v[i][1];
        if (i == 0 && row < 64) { __syncwarp(); if (lane == 0) red_release(&g_ln0); }
      }
    }
  }
  if (tid == 0) {
    for (int i = 0; i < G_STAGES; i++) { mbar_init(fullb + 8 * i, 1); mbar_init(emptyb + 8 * i, 2); }
    mbar_init(wbar, 1);
    for (int i = 0; i < 12; i++) mbar_init(full2 + 8 * i, 1);
    for (int i = 0; i < 3; i++) mbar_init(empty2 + 8 * i, 2);
    sts32(done2, 0); sts32(done2 + 4, 0);
    asm volatile("fence.mbarrier_init.release.cluster;" ::: "memory");
  }
  __syncthreads();
  if (tid == 64) { GT(200 + j, 3); red_release(&g_lncnt); GT(100 + j, 7); }
  const uint32_t ep = lds32(done2 + 8);
  const int nup = (176 - j + NHELP - 1) / NHELP;
  const int nit = nup + (j < 32 ? 1 : 0);
  if (warp < 4) {
    reg_dec<88>();
    if (tid == 0) {
      int st = 0, ph = 0;
      poll_ge(&g_lncnt, ep * NHELP);
      fence_async_all();
      { const uint32_t t0 = clk32(); while (clk32() - t0 < HELP_DELAY) {} }
      for (int n = 0; n < nit; n++) {
        const bool up = n < nup;
        const int item = j + n * NHELP;
        const int blk = up ? item / 11 : j >> 1, nt = up ? item % 11 : j & 1;
        const int nk = up ? 8 : HCH;
        if (!up) { GT(100 + j, 1); poll_ge(&g_hcnt[blk], ep * 22); fence_async_all(); GT(100 + j, 2); }
        for (int kc = 0; kc < nk; kc++) {
          mbar_wait(emptyb + 8 * st, ph ^ 1);
          const uint32_t sa = sb + st * G_STAGE_BYTES, bar = fullb + 8 * st;
          mbar_arrive_tx(bar, G_STAGE_BYTES);
          if (up) {
            bulk_g2s(sa, g_xn + ((size_t)kc * S_TOK + blk * 128) * 128, 16384, bar);
            tma2d(sa + 16384, &tmG, nt * 128, kc * 64, bar);
            tma2d(sa + 16384 + 8192, &tmG, nt * 128 + 64, kc * 64, bar);
            tma2d(sa + 16384 + 16384, &tmU, nt * 128, kc * 64, bar);
            tma2d(sa + 16384 + 24576, &tmU, nt * 128 + 64, kc * 64, bar);
          } else {
            bulk_g2s(sa, g_h + ((size_t)kc * S_TOK + blk * 128) * 128, 16384, bar);
#pragma unroll
            for (int i = 0; i < 4; i++) tma2d(sa + 16384 + i * 8192, &tmD, nt * 256 + i * 64, kc * 64, bar);
          }
          if (++st == G_STAGES) { st = 0; ph ^= 1; }
        }
      }
      if (j < 32) {
        for (int i = 0; i < G_STAGES; i++) {
          mbar_wait(emptyb + 8 * st, ph ^ 1);
          if (++st == G_STAGES) { st = 0; ph ^= 1; }
        }
        GT(100 + j, 3);
        mbar_arrive_tx(wbar, 131072);
        for (int i = 0; i < 16; i++) tma2d(sb + i * 8192, &tmO, cg * 128 + (i >> 3) * 64, ks8 * 512 + (i & 7) * 64, wbar);
        int slot = 0, ready = 0; ph = 0;
        for (int g = 0; g < NSEG; g++) {
          mbar_wait(empty2 + 8 * slot, ph ^ 1);
          if ((g & 3) == 0) poll_ge(&g_dcnt[(g >> 2) * 2 + (cg >> 1)], ep * 3);
#pragma unroll
          for (int q = 0; q < 4; q++) mbar_arrive_tx(full2 + 8 * (slot * 4 + q), 8192);
          if (g >= ready) {
            for (int it = 0; it < 30000; it++) {
              uint32_t r[4];
              asm volatile("ld.acquire.gpu.global.v4.u32 {%0,%1,%2,%3}, [%4];" : "=r"(r[0]), "=r"(r[1]), "=r"(r[2]), "=r"(r[3])
                           : "l"(&g_cnt[ks8 * NSEG + (g & ~3)]) : "memory");
              ready = g;
#pragma unroll
              for (int i = 0; i < 4; i++) if (ready == (g & ~3) + i && (int)(r[i] - ep * 8) >= 0) ready++;
              if (ready > g) break;
            }
            fence_async_all();
          }
          if (g == 63) GT(100 + j, 4);
          const unsigned char* src = g_ox + ((size_t)(ks8 * 8) * S_TOK + g * 32) * 128;
#pragma unroll
          for (int kc = 0; kc < 8; kc++)
            bulk_g2s(sb + G_SM_RING + slot * 32768 + kc * 4096, src + (size_t)kc * S_TOK * 128, 4096, full2 + 8 * (slot * 4 + (kc >> 1)));
          if (++slot == 3) { slot = 0; ph ^= 1; }
        }
      }
    } else if (warp == 1 && j < 32) {
      {
        unsigned char* dst = g_acc + (size_t)((j >> 1) * 4 * 32 + (j & 1) * 16) * 1536 + lane * 16;
#pragma unroll 1
        for (int g = 0; g < 4; g++)
#pragma unroll 8
          for (int i = 0; i < 48; i++) *reinterpret_cast<uint4*>(dst + g * 32 * 1536 + i * 512) = make_uint4(0u, 0u, 0u, 0u);
        __syncwarp();
        if (lane == 0) red_release(&g_dcnt[j]);
      }
      const int col = cg * 128 + ks8 * 16;
      const uint32_t fs = sb + G_SM_FIN;
#pragma unroll 1
      for (int g = 0; g < NSEG; g++) {
        if ((g & 3) == 0) poll_ge(&g_dcnt[(g >> 2) * 2 + (cg >> 1)], ep * 3);
        float4 f[4];
        const float4* fp = reinterpret_cast<const float4*>(g_ffn + (size_t)(g * 32 + lane) * DM + col);
#pragma unroll
        for (int i = 0; i < 4; i++) f[i] = __ldcg(fp + i);
        for (int it = 0; it < 400000; it++) {
          uint32_t d0, d1;
          asm volatile("ld.volatile.shared.v2.b32 {%0,%1}, [%2];" : "=r"(d0), "=r"(d1) : "r"(done2) : "memory");
          if ((int)min(d0, d1) > g) break;
          __nanosleep(20);
        }
        const unsigned char* ap = g_acc + (size_t)(g * 32 + cg * 8 + ks8) * 1536 + lane * 16;
        uint32_t v[3][4];
        for (int it = 0;; it++) {
#pragma unroll
          for (int i = 0; i < 3; i++)
            asm volatile("ld.relaxed.gpu.global.v4.b32 {%0,%1,%2,%3}, [%4];" : "=r"(v[i][0]), "=r"(v[i][1]), "=r"(v[i][2]), "=r"(v[i][3]) : "l"(ap + i * 512) : "memory");
          if (__all_sync(0xffffffffu, v[0][3] == 0x4800u && v[1][3] == 0x4800u && v[2][3] == 0x4800u)) break;
          if (it > 30000) { *(volatile unsigned int*)&g_err = 4; break; }
        }
        const uint32_t ra = fs + (lane >> 3) * 256 + (lane & 7) * 32;
        stsm4t(ra, v[0][0], v[0][1], v[0][2], v[1][0]);
        stsm4t(ra + 16, v[1][1], v[1][2], v[2][0], v[2][1]);
        __syncwarp();
        uint32_t t[8];
        lds128(fs + lane * 32, t); lds128(fs + lane * 32 + 16, t + 4);
        __syncwarp();
        uint32_t o[8];
#pragma unroll
        for (int i = 0; i < 4; i++) {
          const float2 a = __half22float2(*reinterpret_cast<__half2*>(&t[2 * i])), b = __half22float2(*reinterpret_cast<__half2*>(&t[2 * i + 1]));
          o[2 * i] = pack_bf16(f[i].x + a.x, f[i].y + a.y);
          o[2 * i + 1] = pack_bf16(f[i].z + b.x, f[i].w + b.y);
        }
        uint4* op = reinterpret_cast<uint4*>(out + (size_t)(g * 32 + lane) * DM + col);
        op[0] = make_uint4(o[0], o[1], o[2], o[3]);
        op[1] = make_uint4(o[4], o[5], o[6], o[7]);
        if (lane == 0) GT(100 + j, 8 + g);
      }
      pdl_wait();
      if (lane == 0) GT(100 + j, 6);
    }
  } else {
    reg_inc<208>();
    const int wg = (warp >> 2) - 1;
    const bool lead = (tid & 127) == 0;
    {
      float c[128];
      int st = 0, ph = 0;
      int pend = -1;
      for (int n = 0; n < nit; n++) {
        const bool up = n < nup;
        const int item = j + n * NHELP;
        const int blk = up ? item / 11 : j >> 1, nt = up ? item % 11 : j & 1;
        const int nk = up ? 8 : HCH;
        if (!up && lead) { bulk_wait_all(); fence_async_all(); red_release(&g_hcnt[pend]); }
        int prev = -1;
        for (int kc = 0; kc < nk; kc++) {
          mbar_wait(fullb + 8 * st, ph);
          const uint32_t sa = sb + st * G_STAGE_BYTES;
          wg_fence();
#pragma unroll
          for (int ks = 0; ks < 4; ks++)
            wgmma_ss_n256(c, mkdesc(sa + wg * 8192 + ks * 32, 16, 1024), mkdesc(sa + 16384 + ks * 2048, 8192, 1024), kc | ks);
          wg_commit();
          if (prev >= 0) { wg_wait<1>(); if (lead) mbar_arrive(emptyb + 8 * prev); }
          prev = st;
          if (++st == G_STAGES) { st = 0; ph ^= 1; }
        }
        wg_wait<0>();
        if (lead) mbar_arrive(emptyb + 8 * prev);
        const int wr = (warp & 3) * 16;
        if (up) {
          const uint32_t stg = sb + G_SM_HST + wg * 16384;
          if (lead && pend >= 0) { bulk_wait_all(); fence_async_all(); red_release(&g_hcnt[pend]); }
          pend = blk;
          bar_sync(1 + wg, 128);
          const int row = wr + (lane & 7) + ((lane >> 3) & 1) * 8;
#pragma unroll
          for (int np = 0; np < 8; np++) {
            uint32_t r[4];
#pragma unroll
            for (int t = 0; t < 2; t++) {
              const int i = (2 * np + t) * 4;
              r[2 * t] = pack_bf16(bfr(c[i]) * bfr(c[64 + i]), bfr(c[i + 1]) * bfr(c[64 + i + 1]));
              r[2 * t + 1] = pack_bf16(bfr(c[i + 2]) * bfr(c[64 + i + 2]), bfr(c[i + 3]) * bfr(c[64 + i + 3]));
            }
            const int c16 = 2 * np + (lane >> 4);
            stsm4(stg + (c16 >> 3) * 8192 + row * 128 + (((c16 & 7) ^ (row & 7)) << 4), r[0], r[1], r[2], r[3]);
          }
          fence_async_smem();
          bar_sync(1 + wg, 128);
          if (lead) {
            unsigned char* dst = g_h + ((size_t)(nt * 2) * S_TOK + blk * 128 + wg * 64) * 128;
            bulk_s2g(dst, stg, 8192);
            bulk_s2g(dst + (size_t)S_TOK * 128, stg + 8192, 8192);
            bulk_commit();
            if (n == nit - 1) { bulk_wait_all(); fence_async_all(); red_release(&g_hcnt[blk]); }
          }
        } else {
          const int r0 = blk * 128 + wg * 64 + wr + (lane >> 2);
          const int c0 = nt * 256 + (lane & 3) * 2;
#pragma unroll
          for (int i = 0; i < 32; i++) {
            const size_t o0 = (size_t)r0 * DM + c0 + i * 8, o1 = o0 + 8 * DM;
            const uint32_t x0 = *reinterpret_cast<const uint32_t*>(x + o0), x1 = *reinterpret_cast<const uint32_t*>(x + o1);
            *reinterpret_cast<float2*>(g_ffn + o0) = make_float2(bf_lo(x0) + c[4 * i], bf_hi(x0) + c[4 * i + 1]);
            *reinterpret_cast<float2*>(g_ffn + o1) = make_float2(bf_lo(x1) + c[4 * i + 2], bf_hi(x1) + c[4 * i + 3]);
          }
          bar_sync(1 + wg, 128);
          if (lead) red_release(&g_dcnt[j]);
        }
      }
    }
    if (j < 32) {
      uint32_t W[32][4];
      mbar_wait(wbar, 0);
      {
        const int kr = (lane & 7) + ((lane >> 4) << 3), ch = (warp & 3) * 2 + ((lane >> 3) & 1);
        const uint32_t a0 = sb + wg * 65536 + kr * 128 + ((ch ^ (kr & 7)) << 4);
#pragma unroll
        for (int ks = 0; ks < 32; ks++) ldsm4t(a0 + ks * 2048, W[ks]);
      }
      unsigned char* ap = g_acc + (size_t)(cg * 8 + warp - 4) * 1536 + lane * 16;
      int slot = 0, ph = 0;
#pragma unroll 1
      for (int g = 0; g < NSEG; g++) {
        float c[16];
        const uint32_t dlo = (((sb + G_SM_RING + slot * 32768) & 0x3FFFF) >> 4) | (1u << 16);
#pragma unroll
        for (int q = 0; q < 4; q++) {
          mbar_wait(full2 + 8 * (slot * 4 + q), ph);
          if (q == 0) wg_fence();
#pragma unroll
          for (int ks = q * 8; ks < q * 8 + 8; ks++)
            wgmma_rs_n32(c, W[ks], ((uint64_t)0x40000040u << 32) | (uint64_t)(dlo + (ks >> 2) * 256 + (ks & 3) * 2), ks);
        }
        wg_commit();
        wg_wait<0>();
        if (lead) mbar_arrive(empty2 + 8 * slot);
        uint32_t w[9];
#pragma unroll
        for (int nt = 0; nt < 4; nt++) { w[nt] = pack_f16(c[4 * nt], c[4 * nt + 1]); w[4 + nt] = pack_f16(c[4 * nt + 2], c[4 * nt + 3]); }
        w[8] = 0;
#pragma unroll
        for (int i = 0; i < 3; i++)
          asm volatile("red.relaxed.gpu.global.add.noftz.v4.f16x2 [%0], {%1,%2,%3,%4};"
                       ::"l"(ap + i * 512), "r"(w[3 * i]), "r"(w[3 * i + 1]), "r"(w[3 * i + 2]), "r"(0x3c00u) : "memory");
        if (lead) asm volatile("st.volatile.shared.b32 [%0], %1;" ::"r"(done2 + wg * 4), "r"(g + 1) : "memory");
        if (lead && wg == 0 && g == 63) GT(100 + j, 5);
        ap += 32 * 1536;
        if (++slot == 3) { slot = 0; ph ^= 1; }
      }
    }
  }
}

typedef CUresult (*EncodeFn)(CUtensorMap*, CUtensorMapDataType, cuuint32_t, void*, const cuuint64_t*, const cuuint64_t*,
                             const cuuint32_t*, const cuuint32_t*, CUtensorMapInterleave, CUtensorMapSwizzle,
                             CUtensorMapL2promotion, CUtensorMapFloatOOBfill);

void make_map(EncodeFn fn, CUtensorMap* m, const void* p, int rows, int cols, int bc = 64, int br = 64) {
  cuuint64_t dims[2] = {(cuuint64_t)cols, (cuuint64_t)rows};
  cuuint64_t strides[1] = {(cuuint64_t)cols * 2};
  cuuint32_t box[2] = {(cuuint32_t)bc, (cuuint32_t)br}, es[2] = {1, 1};
  fn(m, CU_TENSOR_MAP_DATA_TYPE_BFLOAT16, 2, const_cast<void*>(p), dims, strides, box, es, CU_TENSOR_MAP_INTERLEAVE_NONE,
     bc == 64 ? CU_TENSOR_MAP_SWIZZLE_128B : bc == 32 ? CU_TENSOR_MAP_SWIZZLE_64B : CU_TENSOR_MAP_SWIZZLE_NONE,
     CU_TENSOR_MAP_L2_PROMOTION_L2_256B, CU_TENSOR_MAP_FLOAT_OOB_FILL_NONE);
}

}

extern "C" void kernel_launch(void* const* d_in, const int* in_sizes, int n_in, void* d_out, int out_size) {
  (void)in_sizes; (void)n_in; (void)out_size;
  const __nv_bfloat16* x = (const __nv_bfloat16*)d_in[0];
  const __nv_bfloat16* mem0 = (const __nv_bfloat16*)d_in[1];
  const __nv_bfloat16* Wq = (const __nv_bfloat16*)d_in[2];
  const __nv_bfloat16* Wk = (const __nv_bfloat16*)d_in[3];
  const __nv_bfloat16* Wv = (const __nv_bfloat16*)d_in[4];
  const __nv_bfloat16* Wo = (const __nv_bfloat16*)d_in[5];
  __nv_bfloat16* out = (__nv_bfloat16*)d_out;

  static EncodeFn enc = nullptr;
  if (!enc) {
    void* fn = nullptr; cudaDriverEntryPointQueryResult qr;
    cudaGetDriverEntryPoint("cuTensorMapEncodeTiled", &fn, cudaEnableDefault, &qr);
    enc = (EncodeFn)fn;
    cudaFuncSetAttribute(k_chain, cudaFuncAttributeMaxDynamicSharedMemorySize, SM_END);
    cudaFuncSetAttribute(k_help, cudaFuncAttributeMaxDynamicSharedMemorySize, G_SM_END);
  }
  CUtensorMap tmG, tmU, tmD, tmO;
  make_map(enc, &tmG, d_in[8], DM, FF);
  make_map(enc, &tmU, d_in[9], DM, FF);
  make_map(enc, &tmD, d_in[10], FF, DM);
  make_map(enc, &tmO, Wo, NH * DH, DM);
  WMaps wm;
  make_map(enc, &wm.q48, Wq, DM, NH * DH, 48, 64); make_map(enc, &wm.k48, Wk, DM, NH * DH, 48, 64);
  make_map(enc, &wm.q32, Wq, DM, NH * DH, 32, 64); make_map(enc, &wm.k32, Wk, DM, NH * DH, 32, 64);
  make_map(enc, &wm.v32, Wv, DM, NH * DH, 32, 64); make_map(enc, &wm.v64, Wv, DM, NH * DH, 64, 64);
  make_map(enc, &wm.o64, Wo, NH * DH, DM, 64, 64); make_map(enc, &wm.o32, Wo, NH * DH, DM, 32, 64);

  cudaStream_t st = cudaStreamPerThread;
  {
    cudaLaunchConfig_t cfg = {};
    cfg.gridDim = dim3(NCL * CLS); cfg.blockDim = dim3(512); cfg.dynamicSmemBytes = SM_END; cfg.stream = st;
    cudaLaunchAttribute at[1];
    at[0].id = cudaLaunchAttributeClusterDimension; at[0].val.clusterDim.x = CLS; at[0].val.clusterDim.y = 1; at[0].val.clusterDim.z = 1;
    cfg.attrs = at; cfg.numAttrs = 1;
    cudaLaunchKernelEx(&cfg, k_chain, wm, mem0, x);
  }
  {
    cudaLaunchConfig_t cfg = {};
    cfg.gridDim = dim3(NHELP); cfg.blockDim = dim3(384); cfg.dynamicSmemBytes = G_SM_END; cfg.stream = st;
    cudaLaunchAttribute at[1];
    at[0].id = cudaLaunchAttributeProgrammaticStreamSerialization; at[0].val.programmaticStreamSerializationAllowed = 1;
    cfg.attrs = at; cfg.numAttrs = 1;
    cudaLaunchKernelEx(&cfg, k_help, tmG, tmU, tmD, tmO, x, out);
  }
}
```

```cpp
#include <cuda_runtime.h>
#include <cuda_bf16.h>
#include <cuda_fp16.h>
#include <cuda.h>
#include <stdint.h>

namespace {

constexpr int S_TOK = 2048, DM = 512, NH = 32, DH = 128, NSEG = 64, FF = 1376;
constexpr int NCL = 16, CLS = 6;
constexpr int NHELP = 36;
constexpr int NCTA = NCL * CLS + NHELP;
constexpr int NVST = 4;
constexpr int HCH = 22;

__device__ __align__(1024) unsigned char g_xn[8 * S_TOK * 128];
__device__ __align__(1024) unsigned char g_ox[64 * S_TOK * 128];
__device__ __align__(1024) unsigned char g_h[HCH * S_TOK * 128];
__device__ __align__(1024) unsigned char g_q[8 * NH * 8192];
__device__ __align__(1024) unsigned char g_k[8 * NH * 8192];
__device__ __align__(1024) unsigned char g_v[4 * NCL * 16384];
constexpr int EX_WARP = 1024, EX_RANK = 4 * EX_WARP, EX_BUF = CLS * EX_RANK;
__device__ __align__(1024) unsigned char g_ex[4 * EX_BUF];
__device__ __align__(1024) unsigned char g_acc[NSEG * 32 * 1536];
__device__ __align__(1024) float g_ffn[S_TOK * DM];
__device__ unsigned int g_done;
__device__ unsigned int g_ln0;
__device__ unsigned int g_ln1;
__device__ unsigned int g_lncnt;
__device__ __align__(16) unsigned int g_cnt[8 * NSEG];
__device__ unsigned int g_hcnt[16];
__device__ unsigned int g_dcnt[32];
__device__ unsigned int g_err;
#define GT(row, slot) do {} while (0)

__device__ __forceinline__ uint32_t smem_u32(const void* p) { return (uint32_t)__cvta_generic_to_shared(p); }
__device__ __forceinline__ uint32_t mapa(uint32_t a, uint32_t r) {
  uint32_t o; asm volatile("mapa.shared::cluster.u32 %0, %1, %2;" : "=r"(o) : "r"(a), "r"(r)); return o;
}
__device__ __forceinline__ void mbar_init(uint32_t bar, uint32_t cnt) {
  asm volatile("mbarrier.init.shared::cta.b64 [%0], %1;" ::"r"(bar), "r"(cnt) : "memory");
}
__device__ __forceinline__ void mbar_arrive(uint32_t bar) {
  asm volatile("mbarrier.arrive.shared::cta.b64 _, [%0];" ::"r"(bar) : "memory");
}
__device__ __forceinline__ void mbar_arrive_tx(uint32_t bar, uint32_t bytes) {
  asm volatile("mbarrier.arrive.expect_tx.shared::cta.b64 _, [%0], %1;" ::"r"(bar), "r"(bytes) : "memory");
}
__device__ __forceinline__ void mbar_arrive_remote(uint32_t cbar) {
  asm volatile("mbarrier.arrive.shared::cluster.b64 _, [%0];" ::"r"(cbar) : "memory");
}
__device__ __forceinline__ void mbar_arrive_remote_rel(uint32_t cbar) {
  asm volatile("mbarrier.arrive.release.cluster.shared::cluster.b64 _, [%0];" ::"r"(cbar) : "memory");
}
__device__ __forceinline__ bool mbar_try(uint32_t bar, uint32_t par) {
  uint32_t ok;
  asm volatile("{\n.reg .pred p;\nmbarrier.try_wait.parity.shared::cta.b64 p, [%1], %2;\nselp.u32 %0, 1, 0, p;\n}"
               : "=r"(ok) : "r"(bar), "r"(par) : "memory");
  return ok;
}
__device__ __forceinline__ bool mbar_try_t(uint32_t bar, uint32_t par) {
  uint32_t ok;
  asm volatile("{\n.reg .pred p;\nmbarrier.try_wait.parity.shared::cta.b64 p, [%1], %2, 1000;\nselp.u32 %0, 1, 0, p;\n}"
               : "=r"(ok) : "r"(bar), "r"(par) : "memory");
  return ok;
}
__device__ __forceinline__ bool mbar_try_acq(uint32_t bar, uint32_t par) {
  uint32_t ok;
  asm volatile("{\n.reg .pred p;\nmbarrier.try_wait.parity.acquire.cluster.shared::cta.b64 p, [%1], %2;\nselp.u32 %0, 1, 0, p;\n}"
               : "=r"(ok) : "r"(bar), "r"(par) : "memory");
  return ok;
}
__device__ __forceinline__ uint32_t clk32m() { uint32_t c; asm volatile("mov.u32 %0, %%clock;" : "=r"(c) :: "memory"); return c; }
__device__ __forceinline__ uint32_t clk32() { uint32_t c; asm volatile("mov.u32 %0, %%clock;" : "=r"(c)); return c; }
__device__ __forceinline__ void mbar_wait(uint32_t bar, uint32_t par) {
  asm volatile("{\n.reg .pred p, q;\n.reg .b32 c;\nmov.b32 c, 0;\nLW:\n"
               "mbarrier.try_wait.parity.shared::cta.b64 p, [%0], %1;\n"
               "add.u32 c, c, 1;\nsetp.lt.and.u32 q, c, 4096, !p;\n@q bra LW;\n}" ::"r"(bar), "r"(par) : "memory");
}
__device__ __forceinline__ uint32_t mbar_tw(uint32_t bar, uint32_t par, uint32_t off, uint32_t& ok) {
  uint32_t r;
  asm volatile("{\n.reg .pred p;\nmbarrier.try_wait.parity.shared::cta.b64 p, [%2], %3;\nselp.u32 %0, %4, 0, p;\nselp.u32 %1, %1, 0, p;\n}"
               : "=r"(r), "+r"(ok) : "r"(bar), "r"(par), "r"(off) : "memory");
  return r;
}
__device__ __forceinline__ void mbar_hint(uint32_t bar, uint32_t par) {
  const uint32_t t0 = clk32();
  while (!mbar_try_t(bar, par) && clk32() - t0 < 4000) {}
}
__device__ __forceinline__ void mbar_arrive_tx_if(uint32_t bar, uint32_t bytes, bool pred) {
  asm volatile("{\n.reg .pred p;\nsetp.ne.b32 p, %2, 0;\n@p mbarrier.arrive.expect_tx.shared::cta.b64 _, [%0], %1;\n}"
               ::"r"(bar), "r"(bytes), "r"((int)pred) : "memory");
}
__device__ __forceinline__ void bar_sync_if(int id, int n, bool pred) {
  asm volatile("{\n.reg .pred p;\nsetp.ne.b32 p, %2, 0;\n@p bar.sync %0, %1;\n}" ::"r"(id), "r"(n), "r"((int)pred) : "memory");
}
__device__ __forceinline__ void bar_arrive_if(int id, int n, bool pred) {
  asm volatile("{\n.reg .pred p;\nsetp.ne.b32 p, %2, 0;\n@p bar.arrive %0, %1;\n}" ::"r"(id), "r"(n), "r"((int)pred) : "memory");
}
__device__ __forceinline__ void mbar_wait_acq(uint32_t bar, uint32_t par) {
  mbar_wait(bar, par);
  (void)mbar_try_acq(bar, par);
}
__device__ __forceinline__ void st_async32(uint32_t caddr, uint32_t v, uint32_t cbar) {
  asm volatile("st.async.weak.shared::cluster.mbarrier::complete_tx::bytes.b32 [%0], %1, [%2];" ::"r"(caddr), "r"(v), "r"(cbar) : "memory");
}
__device__ __forceinline__ void sts32(uint32_t a, uint32_t v) { asm volatile("st.shared.b32 [%0], %1;" ::"r"(a), "r"(v) : "memory"); }
__device__ __forceinline__ uint32_t lds32(uint32_t a) { uint32_t v; asm volatile("ld.shared.b32 %0, [%1];" : "=r"(v) : "r"(a) : "memory"); return v; }
__device__ __forceinline__ void sts128(uint32_t a, uint32_t x, uint32_t y, uint32_t z, uint32_t w) {
  asm volatile("st.shared.v4.b32 [%0], {%1,%2,%3,%4};" ::"r"(a), "r"(x), "r"(y), "r"(z), "r"(w) : "memory");
}
__device__ __forceinline__ void lds128(uint32_t a, uint32_t* r) {
  asm volatile("ld.shared.v4.b32 {%0,%1,%2,%3}, [%4];" : "=r"(r[0]), "=r"(r[1]), "=r"(r[2]), "=r"(r[3]) : "r"(a) : "memory");
}
__device__ __forceinline__ void ldsm4(uint32_t a, uint32_t* r) {
  asm volatile("ldmatrix.sync.aligned.m8n8.x4.shared.b16 {%0,%1,%2,%3}, [%4];" : "=r"(r[0]), "=r"(r[1]), "=r"(r[2]), "=r"(r[3]) : "r"(a) : "memory");
}
__device__ __forceinline__ void ldsm4t(uint32_t a, uint32_t* r) {
  asm volatile("ldmatrix.sync.aligned.m8n8.x4.trans.shared.b16 {%0,%1,%2,%3}, [%4];" : "=r"(r[0]), "=r"(r[1]), "=r"(r[2]), "=r"(r[3]) : "r"(a) : "memory");
}
__device__ __forceinline__ void ldsm2(uint32_t a, uint32_t* r) {
  asm volatile("ldmatrix.sync.aligned.m8n8.x2.shared.b16 {%0,%1}, [%2];" : "=r"(r[0]), "=r"(r[1]) : "r"(a) : "memory");
}
__device__ __forceinline__ void ldsm2t(uint32_t a, uint32_t* r) {
  asm volatile("ldmatrix.sync.aligned.m8n8.x2.trans.shared.b16 {%0,%1}, [%2];" : "=r"(r[0]), "=r"(r[1]) : "r"(a) : "memory");
}
__device__ __forceinline__ void stsm4(uint32_t a, uint32_t r0, uint32_t r1, uint32_t r2, uint32_t r3) {
  asm volatile("stmatrix.sync.aligned.m8n8.x4.shared.b16 [%0], {%1,%2,%3,%4};" ::"r"(a), "r"(r0), "r"(r1), "r"(r2), "r"(r3) : "memory");
}
__device__ __forceinline__ void stsm4t(uint32_t a, uint32_t r0, uint32_t r1, uint32_t r2, uint32_t r3) {
  asm volatile("stmatrix.sync.aligned.m8n8.x4.trans.shared.b16 [%0], {%1,%2,%3,%4};" ::"r"(a), "r"(r0), "r"(r1), "r"(r2), "r"(r3) : "memory");
}
__device__ __forceinline__ void stsm2t(uint32_t a, uint32_t r0, uint32_t r1) {
  asm volatile("stmatrix.sync.aligned.m8n8.x2.trans.shared.b16 [%0], {%1,%2};" ::"r"(a), "r"(r0), "r"(r1) : "memory");
}
__device__ __forceinline__ void mma16816(float* c, const uint32_t* a, uint32_t b0, uint32_t b1) {
  asm volatile("mma.sync.aligned.m16n8k16.row.col.f32.bf16.bf16.f32 {%0,%1,%2,%3}, {%4,%5,%6,%7}, {%8,%9}, {%0,%1,%2,%3};"
               : "+f"(c[0]), "+f"(c[1]), "+f"(c[2]), "+f"(c[3]) : "r"(a[0]), "r"(a[1]), "r"(a[2]), "r"(a[3]), "r"(b0), "r"(b1));
}
__device__ __forceinline__ void mma16816r(float* c, uint32_t a0, uint32_t a1, uint32_t a2, uint32_t a3, uint32_t b0, uint32_t b1) {
  asm volatile("mma.sync.aligned.m16n8k16.row.col.f32.bf16.bf16.f32 {%0,%1,%2,%3}, {%4,%5,%6,%7}, {%8,%9}, {%0,%1,%2,%3};"
               : "+f"(c[0]), "+f"(c[1]), "+f"(c[2]), "+f"(c[3]) : "r"(a0), "r"(a1), "r"(a2), "r"(a3), "r"(b0), "r"(b1));
}
__device__ __forceinline__ void mma1688(float* c, uint32_t a0, uint32_t a1, uint32_t b0) {
  asm volatile("mma.sync.aligned.m16n8k8.row.col.f32.bf16.bf16.f32 {%0,%1,%2,%3}, {%4,%5}, {%6}, {%0,%1,%2,%3};"
               : "+f"(c[0]), "+f"(c[1]), "+f"(c[2]), "+f"(c[3]) : "r"(a0), "r"(a1), "r"(b0));
}
__device__ __forceinline__ void hmma16816(float* c, uint32_t a0, uint32_t a1, uint32_t a2, uint32_t a3, uint32_t b0, uint32_t b1) {
  asm volatile("mma.sync.aligned.m16n8k16.row.col.f32.f16.f16.f32 {%0,%1,%2,%3}, {%4,%5,%6,%7}, {%8,%9}, {%0,%1,%2,%3};"
               : "+f"(c[0]), "+f"(c[1]), "+f"(c[2]), "+f"(c[3]) : "r"(a0), "r"(a1), "r"(a2), "r"(a3), "r"(b0), "r"(b1));
}
__device__ __forceinline__ void hmma1688(float* c, uint32_t a0, uint32_t a1, uint32_t b0) {
  asm volatile("mma.sync.aligned.m16n8k8.row.col.f32.f16.f16.f32 {%0,%1,%2,%3}, {%4,%5}, {%6}, {%0,%1,%2,%3};"
               : "+f"(c[0]), "+f"(c[1]), "+f"(c[2]), "+f"(c[3]) : "r"(a0), "r"(a1), "r"(b0));
}
__device__ __forceinline__ void hhmma(uint32_t* c, const uint32_t* a, uint32_t b0, uint32_t b1) {
  asm volatile("mma.sync.aligned.m16n8k16.row.col.f16.f16.f16.f16 {%0,%1}, {%2,%3,%4,%5}, {%6,%7}, {%0,%1};"
               : "+r"(c[0]), "+r"(c[1]) : "r"(a[0]), "r"(a[1]), "r"(a[2]), "r"(a[3]), "r"(b0), "r"(b1));
}
__device__ __forceinline__ void hhmma8(uint32_t* c, uint32_t a0, uint32_t a1, uint32_t b0) {
  asm volatile("mma.sync.aligned.m16n8k8.row.col.f16.f16.f16.f16 {%0,%1}, {%2,%3}, {%4}, {%0,%1};"
               : "+r"(c[0]), "+r"(c[1]) : "r"(a0), "r"(a1), "r"(b0));
}
__device__ __forceinline__ uint32_t hmul2u(uint32_t x, uint32_t y) { uint32_t r; asm("mul.rn.f16x2 %0, %1, %2;" : "=r"(r) : "r"(x), "r"(y)); return r; }
__device__ __forceinline__ uint32_t hfma2u(uint32_t x, uint32_t y, uint32_t z) { uint32_t r; asm("fma.rn.f16x2 %0, %1, %2, %3;" : "=r"(r) : "r"(x), "r"(y), "r"(z)); return r; }
__device__ __forceinline__ uint32_t hadd2u(uint32_t x, uint32_t y) { uint32_t r; asm("add.rn.f16x2 %0, %1, %2;" : "=r"(r) : "r"(x), "r"(y)); return r; }
__device__ __forceinline__ uint32_t ex2_h2(uint32_t x) { uint32_t y; asm("ex2.approx.f16x2 %0, %1;" : "=r"(y) : "r"(x)); return y; }
__device__ __forceinline__ uint32_t pack_bf16(float lo, float hi) {
  uint32_t r; asm("cvt.rn.bf16x2.f32 %0, %1, %2;" : "=r"(r) : "f"(hi), "f"(lo)); return r;
}
__device__ __forceinline__ uint32_t pack_f16(float lo, float hi) {
  uint32_t r; asm("cvt.rn.f16x2.f32 %0, %1, %2;" : "=r"(r) : "f"(hi), "f"(lo)); return r;
}
__device__ __forceinline__ uint32_t f16_to_bf16(uint32_t h) {
  float lo, hi;
  asm("{\n.reg .b16 l, h;\nmov.b32 {l, h}, %2;\ncvt.f32.f16 %0, l;\ncvt.f32.f16 %1, h;\n}" : "=f"(lo), "=f"(hi) : "r"(h));
  uint32_t r; asm("cvt.rn.bf16x2.f32 %0, %1, %2;" : "=r"(r) : "f"(hi), "f"(lo)); return r;
}
__device__ __forceinline__ float bf_lo(uint32_t w) { return __uint_as_float(w << 16); }
__device__ __forceinline__ float bf_hi(uint32_t w) { return __uint_as_float(w & 0xffff0000u); }
__device__ __forceinline__ uint32_t bf16_to_f16(uint32_t w) { return pack_f16(bf_lo(w), bf_hi(w)); }
__device__ __forceinline__ float2 h2f2(uint32_t w) { return __half22float2(*reinterpret_cast<__half2*>(&w)); }
__device__ __forceinline__ float ex2(float x) { float y; asm("ex2.approx.ftz.f32 %0, %1;" : "=f"(y) : "f"(x)); return y; }
__device__ __forceinline__ float rcp(float x) { float y; asm("rcp.approx.ftz.f32 %0, %1;" : "=f"(y) : "f"(x)); return y; }
__device__ __forceinline__ void bar_sync(int id, int n) { asm volatile("bar.sync %0, %1;" ::"r"(id), "r"(n) : "memory"); }
__device__ __forceinline__ void bar_arrive(int id, int n) { asm volatile("bar.arrive %0, %1;" ::"r"(id), "r"(n) : "memory"); }
__device__ __forceinline__ void fence_async_smem() { asm volatile("fence.proxy.async.shared::cta;" ::: "memory"); }
__device__ __forceinline__ void fence_async_all() { asm volatile("fence.proxy.async.global;" ::: "memory"); }
__device__ __forceinline__ void cp_async16(uint32_t dst, const void* src) {
  asm volatile("cp.async.cg.shared.global [%0], [%1], 16;" ::"r"(dst), "l"(src) : "memory");
}
__device__ __forceinline__ void cp_async16p(uint32_t dst, const void* src) {
  asm volatile("cp.async.cg.shared.global.L2::128B [%0], [%1], 16;" ::"r"(dst), "l"(src) : "memory");
}
__device__ __forceinline__ void prefetch_l2(const void* src, uint32_t bytes) {
  asm volatile("cp.async.bulk.prefetch.L2.global [%0], %1;" ::"l"(src), "r"(bytes) : "memory");
}
__device__ __forceinline__ void cp_async_wait_all() { asm volatile("cp.async.wait_all;" ::: "memory"); }
__device__ __forceinline__ void bulk_g2s(uint32_t dst, const void* src, uint32_t bytes, uint32_t bar) {
  asm volatile("cp.async.bulk.shared::cluster.global.mbarrier::complete_tx::bytes [%0], [%1], %2, [%3];"
               ::"r"(dst), "l"(src), "r"(bytes), "r"(bar) : "memory");
}
__device__ __forceinline__ void bulk_g2s_mc(uint32_t dst, const void* src, uint32_t bytes, uint32_t bar, uint16_t mask) {
  asm volatile("cp.async.bulk.shared::cluster.global.mbarrier::complete_tx::bytes.multicast::cluster [%0], [%1], %2, [%3], %4;"
               ::"r"(dst), "l"(src), "r"(bytes), "r"(bar), "h"(mask) : "memory");
}
__device__ __forceinline__ void bulk_s2g(void* dst, uint32_t src, uint32_t bytes) {
  asm volatile("cp.async.bulk.global.shared::cta.bulk_group [%0], [%1], %2;" ::"l"(dst), "r"(src), "r"(bytes) : "memory");
}
__device__ __forceinline__ void bulk_commit() { asm volatile("cp.async.bulk.commit_group;" ::: "memory"); }
__device__ __forceinline__ void bulk_wait_read() { asm volatile("cp.async.bulk.wait_group.read 0;" ::: "memory"); }
__device__ __forceinline__ void bulk_wait_all() { asm volatile("cp.async.bulk.wait_group 0;" ::: "memory"); }
__device__ __forceinline__ void tma2d(uint32_t dst, const CUtensorMap* m, int c0, int c1, uint32_t bar) {
  asm volatile("cp.async.bulk.tensor.2d.shared::cluster.global.mbarrier::complete_tx::bytes [%0], [%1, {%3, %4}], [%2];"
               ::"r"(dst), "l"(m), "r"(bar), "r"(c0), "r"(c1) : "memory");
}
__device__ __forceinline__ void pdl_wait() { asm volatile("griddepcontrol.wait;" ::: "memory"); }
__device__ __forceinline__ void pdl_launch() { asm volatile("griddepcontrol.launch_dependents;" ::: "memory"); }
__device__ __forceinline__ void cluster_sync() {
  asm volatile("barrier.cluster.arrive.aligned;\nbarrier.cluster.wait.aligned;" ::: "memory");
}
__device__ __forceinline__ void cluster_arrive_rlx() { asm volatile("barrier.cluster.arrive.relaxed.aligned;" ::: "memory"); }
__device__ __forceinline__ void cluster_wait() { asm volatile("barrier.cluster.wait.aligned;" ::: "memory"); }
__device__ __forceinline__ void red_release(unsigned int* p) {
  asm volatile("red.release.gpu.global.add.u32 [%0], 1;" ::"l"(p) : "memory");
}
__device__ __forceinline__ void poll_ge(const unsigned int* p, unsigned int v) {
  for (int it = 0; it < 30000; it++) {
    unsigned int r;
    asm volatile("ld.acquire.gpu.global.u32 %0, [%1];" : "=r"(r) : "l"(p) : "memory");
    if ((int)(r - v) >= 0) return;
  }
  *(volatile unsigned int*)&g_err = 3;
}
__device__ __forceinline__ uint64_t mkdesc(uint32_t saddr, uint32_t lbo, uint32_t sbo) {
  return (uint64_t)((saddr & 0x3FFFF) >> 4) | ((uint64_t)(lbo >> 4) << 16) | ((uint64_t)(sbo >> 4) << 32) | ((uint64_t)1 << 62);
}
__device__ __forceinline__ void wg_fence() { asm volatile("wgmma.fence.sync.aligned;" ::: "memory"); }
__device__ __forceinline__ void wg_commit() { asm volatile("wgmma.commit_group.sync.aligned;" ::: "memory"); }
template <int N> __device__ __forceinline__ void wg_wait() { asm volatile("wgmma.wait_group.sync.aligned %0;" ::"n"(N) : "memory"); }
__device__ __forceinline__ void wgmma_rs_n32(float* c, const uint32_t* a, uint64_t d, int acc) {
  asm volatile("{\n.reg .pred p;\nsetp.ne.b32 p, %21, 0;\n"
    "wgmma.mma_async.sync.aligned.m64n32k16.f32.bf16.bf16 {%0,%1,%2,%3,%4,%5,%6,%7,%8,%9,%10,%11,%12,%13,%14,%15}, {%16,%17,%18,%19}, %20, p, 1, 1, 0;\n}"
    : "+f"(c[0]), "+f"(c[1]), "+f"(c[2]), "+f"(c[3]), "+f"(c[4]), "+f"(c[5]), "+f"(c[6]), "+f"(c[7]),
      "+f"(c[8]), "+f"(c[9]), "+f"(c[10]), "+f"(c[11]), "+f"(c[12]), "+f"(c[13]), "+f"(c[14]), "+f"(c[15])
    : "r"(a[0]), "r"(a[1]), "r"(a[2]), "r"(a[3]), "l"(d), "r"(acc));
}
template <int R> __device__ __forceinline__ void reg_inc() { asm volatile("setmaxnreg.inc.sync.aligned.u32 %0;" ::"n"(R)); }
template <int R> __device__ __forceinline__ void reg_dec() { asm volatile("setmaxnreg.dec.sync.aligned.u32 %0;" ::"n"(R)); }

#define PROF_W(w, slot) do {} while (0)

#define BB_FENCE(K) asm volatile("{\n.reg .pred p;\nsetp.eq.s32 p, %0, %1;\n@p trap;\n}" ::"r"(zu), "n"(ZK + (K)) : "memory")
#define AFENCE(K) do {} while (0)
#define PIN(x) asm volatile("" : "+r"(x))

#define PFN 4
__device__ __forceinline__ float bfr(float x) { return __bfloat162float(__float2bfloat16_rn(x)); }

__device__ __forceinline__ void ln_row(uint4& v0, uint4& v1) {
  float f[16];
  {
    uint32_t w[8] = {v0.x, v0.y, v0.z, v0.w, v1.x, v1.y, v1.z, v1.w};
#pragma unroll
    for (int i = 0; i < 8; i++) { f[2 * i] = bf_lo(w[i]); f[2 * i + 1] = bf_hi(w[i]); }
  }
  float sum = 0.f;
#pragma unroll
  for (int i = 0; i < 16; i++) sum += f[i];
#pragma unroll
  for (int o = 16; o; o >>= 1) sum += __shfl_xor_sync(0xffffffffu, sum, o);
  const float mean = sum * (1.f / DM);
  float sq = 0.f;
#pragma unroll
  for (int i = 0; i < 16; i++) { float d = f[i] - mean; sq += d * d; }
#pragma unroll
  for (int o = 16; o; o >>= 1) sq += __shfl_xor_sync(0xffffffffu, sq, o);
  const float mb = bfr(mean), vb = bfr(sq * (1.f / DM));
  const float rs = 1.f / bfr(sqrtf(bfr(vb + 1e-5f)));
  uint32_t o[8];
#pragma unroll
  for (int i = 0; i < 8; i++) {
    const uint32_t d = pack_bf16(f[2 * i] - mb, f[2 * i + 1] - mb);
    o[i] = pack_bf16(bf_lo(d) * rs, bf_hi(d) * rs);
  }
  v0 = make_uint4(o[0], o[1], o[2], o[3]);
  v1 = make_uint4(o[4], o[5], o[6], o[7]);
}

constexpr int SM_BAR = 0;
constexpr int SM_XN = 1024;
constexpr int SM_WO = SM_XN + 32768;
constexpr int SM_MEM = SM_WO + 4096;
constexpr int SM_ATQ = SM_WO + 12288 + 4096;
constexpr int SM_ATK = SM_WO + 2 * 12288 + 4096;
constexpr int SM_OX = SM_WO + 3 * 12288 + 4096;
constexpr int SM_STG = SM_WO + 49152;
constexpr int SM_V = SM_STG;
constexpr int SM_VM = SM_V + NVST * 16384;
constexpr int SM_KX = SM_VM + 4 * 4096;
constexpr int KX_SLOT = 8192 + 1536;
constexpr int SM_KMA = SM_KX + 3 * KX_SLOT;
constexpr int SM_SC = SM_KMA + 2 * 2048;
constexpr int SM_O = SM_SC + 4096;
constexpr int SM_PAIR = SM_O + 4096;
constexpr int SM_LI = SM_PAIR + 1024;
constexpr int SM_SCR = SM_LI + 256;
constexpr int SM_WX = SM_SCR + 4096;
constexpr int SM_SC2 = SM_STG + 131072;
constexpr int SM_PROF = SM_SC2 + 10240;
static_assert(SM_WX + 2048 <= SM_SC2, "staging");
constexpr int SM_END = SM_PROF;
static_assert(SM_END <= 232448, "smem");
static_assert(SM_XN % 1024 == 0 && SM_OX % 1024 == 0, "align");
constexpr int B_MEM = 0;
constexpr int B_SC = 3;
constexpr int B_VM = 4;
constexpr int B_XNF = 8;
constexpr int B_XNE = 9;
constexpr int B_VF = 10;
constexpr int B_VE = 14;
constexpr int B_STF = 18;
constexpr int B_STE = 19;
constexpr int B_ATF = 20;
constexpr int B_KMF = 21;
constexpr int B_QKR = 23;
constexpr int B_WL = 32;
constexpr int B_WO = 29;
constexpr int B_XAF = 25;
constexpr int B_XAE = 26;
constexpr int B_XN1 = 30;
constexpr int B_P3 = 31;
constexpr int SM_EP = 512;
struct WMaps { CUtensorMap q48, k48, q32, k32, v32, v64, o64, o32; };

constexpr float SC_LOG2E = 0.08838834764831845f * 1.4426950408889634f;

#define SPEC
#define DSPEC
#define NB2 320
#define NBF 4
#define ATTN 8
#define NPOLL 2
#define WL_AHEAD 3
#define WO_AFTER 1
#define H2W 0
#define NE1 16
#define POLL_DELAY 330
#define POLL_GAP 240

__global__ void __launch_bounds__(512, 1)
k_chain(const __grid_constant__ WMaps wm, const __nv_bfloat16* __restrict__ mem0, const __nv_bfloat16* __restrict__ x) {
  extern __shared__ __align__(1024) unsigned char smem[];
  const uint32_t sb = smem_u32(smem);
  const int tid = threadIdx.x, lane = tid & 31;
  const int warp = __shfl_sync(0xffffffffu, tid >> 5, 0);
  const int cl = blockIdx.x / CLS;
  const uint32_t rank = blockIdx.x - cl * CLS;
  const int hl = rank / 3, jj = rank - hl * 3;
  const int head = cl * 2 + hl;
  const int nqk = jj < 2 ? 3 : 2, nv = jj < 2 ? 2 : 4;
  const int qk0 = jj * 3, v0 = jj * 2;
  const int nu = rank < 2 ? 12 : 10;
  const int cb = rank < 2 ? rank * 12 : 24 + (rank - 2) * 10;
  auto BAR = [&](int i) { return sb + SM_BAR + 8 * i; };
#define GTR(v) do {} while (0)
  GTR(gt0);
  auto wload = [&](int i) {
    const uint32_t d = sb + SM_STG + i * 16384;
    mbar_arrive_tx(BAR(B_WL + i), 16384);
    tma2d(d, jj < 2 ? &wm.q48 : &wm.q32, head * DH + qk0 * 16, i * 64, BAR(B_WL + i));
    tma2d(d + nqk * 2048, jj < 2 ? &wm.k48 : &wm.k32, head * DH + qk0 * 16, i * 64, BAR(B_WL + i));
    tma2d(d + nqk * 4096, jj < 2 ? &wm.v32 : &wm.v64, head * DH + v0 * 16, i * 64, BAR(B_WL + i));
  };
  if (tid == 480) {
    for (int i = 0; i < 8; i++) mbar_init(BAR(B_WL + i), 1);
    mbar_init(BAR(B_WO), 1);
    asm volatile("fence.mbarrier_init.release.cluster;" ::: "memory");
    GTR(gt1);
#pragma unroll 1
    for (int i = 0; i < WL_AHEAD; i++) wload(i);
    GTR(gt2);
  }
  pdl_launch();
  if (tid < 171 && blockIdx.x * 171 + tid < 16384)
    asm volatile("prefetch.global.L2 [%0];" ::"l"(x + (size_t)(blockIdx.x * 171 + tid) * 64));
  if (tid == 32) sts32(sb + SM_EP, atomicAdd(&g_done, 1u) / NCTA + 1);
  if (tid == 0) {
    mbar_init(BAR(B_MEM + 0), 4); mbar_init(BAR(B_MEM + 1), 4); mbar_init(BAR(B_MEM + 2), nu - 8);
    mbar_init(BAR(B_SC), 5);
    for (int i = 0; i < 4; i++) mbar_init(BAR(B_VM + i), nv);
    mbar_init(BAR(B_XNF), 1); mbar_init(BAR(B_XNE), 2 * CLS);
    mbar_init(BAR(B_XAF), 1); mbar_init(BAR(B_XAE), 2 * CLS);
    for (int i = 0; i < NVST; i++) { mbar_init(BAR(B_VF + i), 1); mbar_init(BAR(B_VE + i), 4); }
    mbar_init(BAR(B_STF), 8); mbar_init(BAR(B_STE), 1);
    mbar_init(BAR(B_ATF), 1); mbar_init(BAR(B_KMF), 1); mbar_init(BAR(B_KMF + 1), 1);
    mbar_init(BAR(B_QKR), 3); mbar_init(BAR(B_QKR + 1), 3);
    mbar_init(BAR(B_XN1), 1);
    mbar_init(BAR(B_P3), 4 * CLS);
    asm volatile("fence.mbarrier_init.release.cluster;" ::: "memory");
  }
  __syncthreads();
  GTR(gt3);
  cluster_arrive_rlx();
  GTR(gt4);

  auto scores = [&](uint32_t a_q, uint32_t a_k, uint32_t k3, int kg, uint32_t l16) {
    uint32_t qa[6], kb[6];
    qa[4] = qa[5] = kb[4] = kb[5] = 0;
    ldsm4(a_q, qa);
    ldsm4(a_k, kb);
    float c0[4] = {0.f, 0.f, 0.f, 0.f}, c1[4] = {0.f, 0.f, 0.f, 0.f}, c2[4] = {0.f, 0.f, 0.f, 0.f};
    if (nqk == 3) {
      ldsm2(a_q + 512, qa + 4);
      ldsm2(a_k + k3, kb + 4);
    }
    mma16816r(c0, qa[0], 0u, qa[1], 0u, kb[0], kb[1]);
    mma16816r(c1, qa[2], 0u, qa[3], 0u, kb[2], kb[3]);
    if (nqk == 3) mma16816r(c2, qa[4], 0u, qa[5], 0u, kb[4], kb[5]);
    const uint32_t wv = pack_f16((c0[0] + c1[0] + c2[0]) * SC_LOG2E, (c0[1] + c1[1] + c2[1]) * SC_LOG2E);
    const uint32_t a_sc = sb + SM_SC + rank * 640 + kg * 128 + (l16 >> 2);
#pragma unroll
    for (int d = 1; d < CLS; d++) {
      uint32_t t = rank + d; if (t >= CLS) t -= CLS;
      st_async32(mapa(a_sc, t), wv, mapa(BAR(B_SC), t));
      if (d == 1) bar_arrive(9, 288);
    }
    sts32(a_sc, wv);
    __syncwarp();
    mbar_arrive_tx_if(BAR(B_SC), kg == 0 ? 5 * 640 : 0, l16 == 0);
  };
  auto pv_step = [&](const uint32_t (&p)[5][2], float i0, float i1, int g, int rt, int np) {
    const uint32_t va = sb + SM_V + (g % NVST) * 16384 + hl * 8192 + lane * 16 + np * 1024;
    const int row = (lane & 7) + ((lane >> 3) & 1) * 8;
    uint32_t x0[4], x1[4], xm[2];
    ldsm4(va, x0);
    if (rt) ldsm4(va + 512, x1);
    ldsm2(sb + SM_VM + (g & 3) * 4096 + hl * 2048 + (lane & 15) * 16 + np * 256, xm);
    float o0[4] = {0.f, 0.f, 0.f, 0.f}, o1[4] = {0.f, 0.f, 0.f, 0.f};
    hmma16816(o0, p[0][0], p[0][1], p[1][0], p[1][1], x0[0], x0[2]);
    hmma16816(o1, p[0][0], p[0][1], p[1][0], p[1][1], x0[1], x0[3]);
    if (rt) {
      hmma16816(o0, p[2][0], p[2][1], p[3][0], p[3][1], x1[0], x1[2]);
      hmma16816(o1, p[2][0], p[2][1], p[3][0], p[3][1], x1[1], x1[3]);
    }
    hmma1688(o0, p[4][0], p[4][1], xm[0]);
    hmma1688(o1, p[4][0], p[4][1], xm[1]);
    const int c16 = (2 * np + (lane >> 4));
    stsm4(sb + SM_OX + rt * 4096 + row * 128 + (c16 >> 3) * 2048 + (((c16 & 7) ^ (row & 7)) << 4),
          pack_bf16(o0[0] * i0, o0[1] * i0), pack_bf16(o0[2] * i1, o0[3] * i1),
          pack_bf16(o1[0] * i0, o1[1] * i0), pack_bf16(o1[2] * i1, o1[3] * i1));
  };
  auto ox_publish = [&](int g, int rt) {
    unsigned char* dst = g_ox + ((size_t)(head * 2) * S_TOK + g * 32 + rt * 16) * 128;
    bulk_s2g(dst, sb + SM_OX + rt * 4096, 2048);
    bulk_s2g(dst + (size_t)S_TOK * 128, sb + SM_OX + rt * 4096 + 2048, 2048);
    bulk_commit();
    bulk_wait_all();
    if (rt == 1 && g >= 61) GT(blockIdx.x, 79);
    fence_async_all();
    asm volatile("red.release.gpu.global.add.u32 [%0], 1;" ::"l"(&g_cnt[(head >> 2) * NSEG + g]) : "memory");
    if (rt == 1 && g >= 61) GT(blockIdx.x, 6);
  };
  if (warp < 8) {
    reg_inc<176>();
    uint32_t W[32][4];
    {
      const int kr = (lane & 7) + ((lane >> 4) << 3), ch = (lane >> 3) & 1;
      const int mi = warp < nqk ? 0 : warp < 2 * nqk ? 1 : 2;
      const uint32_t pitch = (mi < 2 ? nqk : nv) * 32;
      uint32_t a0 = kr * pitch + (warp - mi * nqk) * 32 + ch * 16;
      a0 ^= ((a0 >> 7) & (pitch == 96 ? 0u : pitch == 64 ? 3u : 7u)) << 4;
      a0 += sb + SM_STG + mi * nqk * 2048;
      cluster_wait();
#pragma unroll
      for (int q = 0; q < 8; q++) {
        mbar_wait(BAR(B_WL + q), 0);
        if (tid == 0 && (q & 1)) GT(blockIdx.x + 104, 72 + (q >> 1));
#pragma unroll
        for (int ks = 0; ks < 4; ks++) ldsm4t(a0 + q * 16384 + ks * 16 * pitch, W[q * 4 + ks]);
      }
    }
    if (tid == 0) GT(blockIdx.x, 1);
    asm volatile("{\n.reg .b32 t;\nshfl.sync.idx.b32 t, %0, 0, 31, -1;\n}" ::"r"(W[31][3]) : "memory");
    asm volatile("fence.release.sync_restrict::shared::cta.cluster;" ::: "memory");
    cluster_arrive_rlx(); cluster_wait();
    if (tid == 0) GT(blockIdx.x, 2);
    auto opq = [&](uint32_t v) { return (uint32_t)__shfl_sync(0xffffffffu, v, lane); };
    uint32_t l16 = opq(lane * 16);
    const bool isq = warp < nqk, isv = warp >= 2 * nqk;
    const uint32_t x_e = opq(mapa(BAR(B_XNE), 0));
    const int zu = warp;
    constexpr int ZK = -100;
    uint32_t kring = 0;
    uint32_t gring = 0;

#pragma unroll 1
    for (int s_ = -2;; s_++) {
     PIN(l16);
     const int s = __shfl_sync(0xffffffffu, s_, 0);
     const int g = s + 2;
     if (s >= 0) {
      if (s == 0) bar_sync(1, 256);
      const uint32_t par = s & 1, r4 = s & 3;
      float acc[4][4];
      const uint32_t memb = sb + (s == 0 ? SM_SC2 : SM_MEM);
      for (int it = 0; it < 4096; it++) {
#pragma unroll
        for (int i = 0; i < 4; i++) { acc[i][0] = acc[i][1] = acc[i][2] = acc[i][3] = 0.f; }
        uint32_t b[NBF][4];
#define QL(i, o) ldsm4t(memb + (o) + (i) * 512, b[(i) % NBF]);
#define QM(i, k0, k1) mma16816(acc[((i) & 1) * 2], W[k0], b[(i) % NBF][0], b[(i) % NBF][1]); mma16816(acc[((i) & 1) * 2 + 1], W[k1], b[(i) % NBF][2], b[(i) % NBF][3]);
        uint32_t ok1 = 1;
        const uint32_t p0 = mbar_tw(BAR(B_MEM + 0), par, l16, ok1);
        PROF_W(0, 0);
        QL(0, p0) QL(1, p0) QL(2, p0) QL(3, p0)
        QM(0, 0, 1) QL(4, p0) QM(1, 6, 7) QL(5, p0)
        const uint32_t p1 = mbar_tw(BAR(B_MEM + 1), par, l16, ok1);
        QM(2, 12, 13) QL(6, p1) QM(3, 17, 18) QL(7, p1) QM(4, 22, 23) QL(8, p1) QM(5, 27, 28) QL(9, p1)
        QM(6, 2, 3) QL(10, p1) QM(7, 8, 9) QL(11, p1)
        const uint32_t p2 = mbar_tw(BAR(B_MEM + 2), par, l16, ok1);
        QM(8, 14, 15) QL(12, p2) QM(9, 19, 20) QL(13, p2) QM(10, 24, 25) QL(14, p2) QM(11, 29, 30) QL(15, p2)
        const bool ok = __all_sync(0xffffffffu, ok1);
        QM(12, 4, 5) QM(13, 10, 11) QM(14, 16, 21) QM(15, 26, 31)
#undef QL
#undef QM
        if (ok) break;
      }
      const float a0 = (acc[0][0] + acc[1][0]) + (acc[2][0] + acc[3][0]), a1 = (acc[0][1] + acc[1][1]) + (acc[2][1] + acc[3][1]);
      const float a2 = (acc[0][2] + acc[1][2]) + (acc[2][2] + acc[3][2]), a3 = (acc[0][3] + acc[1][3]) + (acc[2][3] + acc[3][3]);
      const uint32_t w0 = pack_bf16(a0, a1), w1 = pack_bf16(a2, a3);
      auto vsend = [&]() {
        const uint32_t w0 = pack_f16(a0, a1), w1 = pack_f16(a2, a3);
        const uint32_t vb = BAR(B_VM + r4), a_out = sb + SM_VM + hl * 2048 + (v0 - 2 * nqk + warp) * 256 + r4 * 4096 + (l16 >> 2);
#pragma unroll
        for (int d = 1; d < CLS; d++) {
          uint32_t t = rank + d; if (t >= CLS) t -= CLS;
          const uint32_t ra = mapa(a_out, t), rb = mapa(vb, t);
          st_async32(ra, w0, rb); st_async32(ra + 128, w1, rb);
        }
        sts32(a_out, w0); sts32(a_out + 128, w1);
        __syncwarp();
        mbar_arrive_tx_if(vb, warp == 7 ? 4096 - nv * 256 : 0, l16 == 0);
      };
      if (!isv) stsm2t(sb + SM_KX + 8192 + kring + warp * 256 + l16, w0, w1);
      uint32_t a_k = sb + SM_KX + nqk * 1024 + warp * 128 + kring + (l16 & 0x70) + ((l16 & 0x180) << 2);
      PIN(a_k);
      bar_arrive_if(2, 320, (warp >> 1) == 2);
      if (isv) vsend();
      auto ksend = [&]() {
        const uint32_t s3 = (uint32_t)s / 3u, own = hl * 3 + (s - s3 * 3), kp = s3 & 1;
        const uint32_t ra = mapa(sb + SM_KMA + kp * 2048 + (qk0 - nqk + warp) * 256 + (l16 >> 2), own), rb = mapa(BAR(B_KMF + kp), own);
        st_async32(ra, w0, rb); st_async32(ra + 128, w1, rb);
      };
      if (warp < 4) {
        bar_sync(2, NB2);
        PROF_W(0, 2);
        if (s != NSEG - 1) scores(sb + SM_KX + 8192 + kring + l16, a_k, 2048, warp, l16);
        if (!isq) ksend();
      }
      else if (!isv) {
        ksend();
      }
      PROF_W(0, 3);
      if (s == NSEG - 1) break;
      kring = kring == 2 * KX_SLOT ? 0u : kring + KX_SLOT;
      if (warp < 4) {
       uint32_t pb[5];
       if (s == 0) mbar_wait(BAR(B_VF), 0);
       for (int it = 0;; it++) {
        uint32_t va[8][4], vm[2][4];
        const uint32_t a_v = sb + SM_V + warp * 4096 + r4 * 16384 + l16;
        ldsm4(a_v, va[0]); ldsm4(a_v + 1024, va[2]); ldsm4(a_v + 2048, va[4]); ldsm4(a_v + 3072, va[6]);
        uint32_t ok1 = 1;
        const uint32_t l3 = (l16 >> 7) * 512 + 512;
        const uint32_t a_ss = sb + SM_SC + (warp >> 1) * 1920 + mbar_tw(BAR(B_SC), par, l16, ok1);
        PROF_W(0, 4);
        __half2 sv[5];
        {
          uint32_t r0[4], r1[4], r2[4], r3[4];
          ldsm4(a_ss, r0); ldsm4(a_ss + 640, r1); ldsm4(a_ss + 1280, r2); ldsm4(a_ss + l3, r3);
#define H2(x) (*reinterpret_cast<__half2*>(&(x)))
#pragma unroll
          for (int i = 0; i < 4; i++) sv[i] = __hadd2(__hadd2(H2(r0[i]), H2(r1[i])), H2(r2[i]));
          sv[4] = __hadd2(__hadd2(H2(r3[0]), H2(r3[1])), H2(r3[2]));
        }
        __half2 mx = __hmax2(__hmax2(__hmax2(sv[0], sv[1]), __hmax2(sv[2], sv[3])), sv[4]);
        mx = __hmax2(mx, __lowhigh2highlow(mx));
        {
          const __half2 m1 = __shfl_xor_sync(0xffffffffu, mx, 1), m2 = __shfl_xor_sync(0xffffffffu, mx, 2), m3 = __shfl_xor_sync(0xffffffffu, mx, 3);
          ldsm4(a_v + 512, va[1]); ldsm4(a_v + 1536, va[3]);
          mx = __hmax2(__hmax2(mx, m1), __hmax2(m2, m3));
        }
#define PEXP(i) { const __half2 d = __hsub2(sv[i], mx); pb[i] = ex2_h2(*reinterpret_cast<const uint32_t*>(&d)); }
        PEXP(0) PEXP(1) PEXP(2) PEXP(3) PEXP(4)
#undef PEXP
#undef H2
        uint32_t o[4][2] = {{0u, 0u}, {0u, 0u}, {0u, 0u}, {0u, 0u}};
        hhmma(o[0], va[0], pb[0], pb[1]); hhmma(o[1], va[2], pb[0], pb[1]);
        ldsm4(a_v + 2560, va[5]); ldsm4(a_v + 3584, va[7]);
        hhmma(o[2], va[4], pb[0], pb[1]); hhmma(o[3], va[6], pb[0], pb[1]);
        const uint32_t a_m = sb + SM_VM + warp * 1024 + r4 * 4096 + mbar_tw(BAR(B_VM + r4), (s >> 2) & 1, l16, ok1);
        PROF_W(0, 13);
        ldsm4(a_m, vm[0]); ldsm4(a_m + 512, vm[1]);
        const bool ok = __all_sync(0xffffffffu, ok1) || it >= 4095;
        hhmma(o[0], va[1], pb[2], pb[3]); hhmma(o[1], va[3], pb[2], pb[3]);
        hhmma(o[2], va[5], pb[2], pb[3]); hhmma(o[3], va[7], pb[2], pb[3]);
        hhmma8(o[0], vm[0][0], vm[0][1], pb[4]); hhmma8(o[1], vm[0][2], vm[0][3], pb[4]);
        hhmma8(o[2], vm[1][0], vm[1][1], pb[4]); hhmma8(o[3], vm[1][2], vm[1][3], pb[4]);
        stsm4(sb + SM_O + warp * 1024 + l16, o[0][0], o[0][1], o[1][0], o[1][1]);
        stsm4(sb + SM_O + warp * 1024 + 512 + l16, o[2][0], o[2][1], o[3][0], o[3][1]);
        bar_arrive_if(3, 256, ok);
        if (ok) break;
       }
       PROF_W(0, 5);
       if ((warp & 1) == 0) {
        const float2 e0 = h2f2(hadd2u(pb[0], pb[1])), e1 = h2f2(hadd2u(pb[2], pb[3])), e2 = h2f2(pb[4]);
        float l = ((e0.x + e0.y) + (e1.x + e1.y)) + (e2.x + e2.y);
        l += __shfl_xor_sync(0xffffffffu, l, 1);
        l += __shfl_xor_sync(0xffffffffu, l, 2);
        if ((l16 & 0x30) == 0) asm volatile("st.shared.u16 [%0], %1;" ::"r"(sb + SM_LI + (warp >> 1) * 128 + (l16 >> 5)), "h"((unsigned short)pack_f16(rcp(l), 0.f)) : "memory");
        bar_arrive(8, 192);
       }
      }
      if (g < NSEG) { mbar_wait(BAR(B_XAF), par ^ 1); if (warp < 4 || NE1 > 16) mbar_wait(BAR(B_XNF), par ^ 1); }
      bar_sync(warp < 4 ? 7 : 9, warp < 4 ? 384 : 288);
      PROF_W(4, 7);
      if (g == NSEG) {
        bar_sync_if(7, 384, warp >= 4);
        mbar_wait(BAR(B_VF + 3), 1);
        continue;
      }
     } else {
      mbar_wait(BAR(g ? B_XN1 : B_XAF), 0);
      mbar_wait(BAR(g ? B_XN1 : B_XNF), 0);
     }
     {
      float c[16];
      uint32_t dlo = ((((sb + SM_XN) & 0x3FFFF) >> 4) | (1u << 16)) + (g == 1 ? (SM_V + 32768 - SM_XN) >> 4 : 0);
      asm volatile("" : "+r"(dlo));
      wg_fence();
#pragma unroll
      for (int ks = 0; ks < 32; ks++) {
        if (ks == NE1) bar_sync_if(7, 384, warp >= 4 && s >= 0);
        wgmma_rs_n32(c, W[ks], ((uint64_t)0x40000040u << 32) | (uint64_t)(dlo + (ks >> 2) * 256 + (ks & 3) * 2), ks);
        if (ks == 15) wg_commit();
      }
      wg_commit();
      const uint32_t d = sb + SM_KX + gring + warp * 1024 + l16;
      gring = gring == 2 * KX_SLOT ? 0u : gring + KX_SLOT;
      const bool rel = l16 == 0 && (warp & 3) == 0 && g != 1 && g < NSEG;
      wg_wait<1>();
      if (rel) mbar_arrive_remote(x_e + 8 * (B_XAE - B_XNE));
      if (g > 0) mbar_wait(BAR(B_STE), (g - 1) & 1);
      if (s >= 0) mbar_wait(BAR(B_VF + ((s + 1) & 3)), ((s + 1) >> 2) & 1);
      wg_wait<0>();
      PROF_W(0, 14);
      PROF_W(4, 12);
      if (rel) mbar_arrive_remote(x_e);
      if (g < NSEG) {
        if (isv) {
          stsm4(d, pack_f16(c[0], c[1]), pack_f16(c[2], c[3]), pack_f16(c[4], c[5]), pack_f16(c[6], c[7]));
          stsm4(d + 512, pack_f16(c[8], c[9]), pack_f16(c[10], c[11]), pack_f16(c[12], c[13]), pack_f16(c[14], c[15]));
        } else {
          stsm4t(d, pack_bf16(c[0], c[1]), pack_bf16(c[4], c[5]), pack_bf16(c[8], c[9]), pack_bf16(c[12], c[13]));
          stsm4t(d + 512, pack_bf16(c[2], c[3]), pack_bf16(c[6], c[7]), pack_bf16(c[10], c[11]), pack_bf16(c[14], c[15]));
        }
        __syncwarp();
        if (l16 == 0) mbar_arrive(BAR(B_STF));
      }
     }
     PROF_W(0, 6);
     PROF_W(4, 15);
    }
    if (jj == (NSEG - 1) % 3) {
      const int rt = warp >> 2;
      uint32_t p[5][2], t[4];
      mbar_wait(BAR(B_VM + 3), 1);
      bar_sync(10, 320);
      const uint32_t a_p = sb + SM_SCR + rt * 1536 + lane * 16;
      lds128(a_p, &p[0][0]); lds128(a_p + 512, &p[2][0]); lds128(a_p + 1024, t);
      p[4][0] = t[0]; p[4][1] = t[1];
      pv_step(p, __uint_as_float(t[2]), __uint_as_float(t[3]), NSEG - 1, rt, (warp & 3) * 2);
      pv_step(p, __uint_as_float(t[2]), __uint_as_float(t[3]), NSEG - 1, rt, (warp & 3) * 2 + 1);
      fence_async_smem();
      bar_sync(11 + rt, 128);
      if ((warp & 3) == 0 && lane == 0) { if (rt == 1) GT(blockIdx.x, 78); ox_publish(NSEG - 1, rt); }
      __syncwarp();
    }
    if (tid == 0) GT(blockIdx.x, 3);
    cluster_sync();
    if (tid == 0) GT(blockIdx.x, 4);
  } else if (warp < 12) {
    reg_dec<112>();
    const int a = warp - 8;
    const uint32_t wo = sb + SM_WO + a * 12288;
    const bool has3 = a + 8 < nu;
    {
      const uint32_t* m0 = reinterpret_cast<const uint32_t*>(mem0) + (lane >> 2) * (DM / 2) + (lane & 3);
      uint32_t m[16];
#pragma unroll
      for (int i = 0; i < 16; i++) {
        const int j = a * 16 + i, k = j - 48;
        const int r = j < 48 ? (j % 24) >> 2 : k < 8 ? k >> 2 : 2 + ((k - 8) >> 1);
        const int o = j < 48 ? (j & 3) + (j < 24 ? 0 : 4) : k < 8 ? 8 + (k & 3) : 8 + (k & 1);
        m[i] = m0[((r < 2 ? r * 12 : 4 + r * 10) + o) * 4];
      }
#pragma unroll
      for (int i = 0; i < 4; i++) stsm4t(sb + SM_SC2 + a * 2048 + i * 512 + lane * 16, m[4 * i], m[4 * i + 1], m[4 * i + 2], m[4 * i + 3]);
      __syncwarp();
      if (lane < (has3 ? 3 : 2)) mbar_arrive(BAR(B_MEM + lane));
    }
    uint32_t R[16][4];
    {
      uint32_t F[8][4];
      const int kr = (lane & 7) + ((lane >> 4) << 3), ch = (lane >> 3) & 1;
      const uint32_t aS = sb + SM_WO + 32768 + (a & 1) * 8192 + kr * 64 + ((((a >> 1) * 2 + ch) ^ ((kr >> 1) & 3)) << 4);
      const uint32_t aF = sb + SM_WO + kr * 128 + (((a + 4 * ch) ^ (kr & 7)) << 4);
      const uint32_t aF0 = aF + (a & 1) * 16384, aF1 = aF + ((a & 1) ^ 1) * 16384;
      cluster_wait(); cluster_arrive_rlx();
      mbar_wait(BAR(B_WO), 0);
      if (tid == 256) GT(blockIdx.x + 104, 76);
#pragma unroll
      for (int u = 0; u < 4; u++) { ldsm4t(aS + (4 + u) * 1024, R[u]); ldsm4t(aF0 + (4 + u) * 2048, R[4 + u]); }
#pragma unroll
      for (int u = 0; u < 8; u++) ldsm4t(aF1 + u * 2048, R[8 + u]);
#pragma unroll
      for (int u = 0; u < 4; u++) { ldsm4t(aS + u * 1024, F[u]); ldsm4t(aF0 + u * 2048, F[4 + u]); }
      bar_sync(4, 128);
#pragma unroll
      for (int u = 0; u < 8; u++) sts128(wo + u * 512 + lane * 16, bf16_to_f16(F[u][0]), bf16_to_f16(F[u][1]), bf16_to_f16(F[u][2]), bf16_to_f16(F[u][3]));
      __syncwarp();
    }
    if (lane < CLS) mbar_arrive_remote(mapa(BAR(B_P3), lane));
#pragma unroll
    for (int u = 0; u < 16; u++) { R[u][0] = bf16_to_f16(R[u][0]); R[u][1] = bf16_to_f16(R[u][1]); R[u][2] = bf16_to_f16(R[u][2]); R[u][3] = bf16_to_f16(R[u][3]); }
    cluster_wait();
    mbar_wait(BAR(B_P3), 0);
    if (tid == 256) GT(blockIdx.x, 5);
    uint32_t l16 = (uint32_t)__shfl_sync(0xffffffffu, lane * 16, lane);

    const int zu = cl;
    constexpr int ZK = 0x1000000;
    const uint32_t u_mem = sb + SM_MEM + (rank * 4 + a) * 128;
    const uint32_t w2off = 6144 + (rank < 2 ? 0 : (4 - 2 * (int)rank) * 128);
    auto send_unit = [&](int wv, uint32_t val) {
      const uint32_t lm = u_mem + (wv < 2 ? wv * 3072 : w2off) + (l16 >> 2);
#pragma unroll
      for (int d = 1; d < CLS; d++) {
        uint32_t t = rank + d; if (t >= CLS) t -= CLS;
        st_async32(mapa(lm, t), val, mapa(BAR(B_MEM + wv), t));
      }
      sts32(lm, val);
      __syncwarp();
      mbar_arrive_tx_if(BAR(B_MEM + wv), a == 0 ? (wv < 2 ? 5 * 512 : (16 - (nu - 8)) * 128) : 0, l16 == 0);
    };
    unsigned char* const exu = g_ex + rank * EX_RANK + a * EX_WARP;
    const uint32_t u_o0 = sb + SM_O + (a & 1) * 2048, u_o1 = sb + SM_O + ((a & 1) ^ 1) * 2048;

#pragma unroll 1
    for (int s = 0;; s++) {
      PIN(l16);
      uint32_t T[8][4];
      const uint32_t u_q = sb + SM_KX + 8192 + ((uint32_t)s % 3u) * KX_SLOT;
      bar_sync(2, NB2);
      if (a == 0 && s != NSEG - 1) scores(u_q + l16, u_q + nqk * 256 + l16, 512, 4, l16);
      if (a == 3 && l16 == 0 && (s < 4 || s > 60)) GT(blockIdx.x, 8 + s);
      if (s == NSEG - 1) {
        if ((int)(l16 >> 5) == cl)
          asm volatile("st.relaxed.gpu.global.v4.b32 [%0], {%1,%1,%1,%1};" ::"l"(exu + EX_BUF + l16), "r"(0u) : "memory");
        mbar_wait(BAR(B_VM + 3), 1);
        break;
      }
#pragma unroll
      for (int u = 0; u < 8; u++) lds128(wo + u * 512 + l16, T[u]);
      bar_sync(3, 256);
      PROF_W(8, 8);
      uint32_t hf[2] = {0u, 0u}, hg[2] = {0u, 0u}, f0[2] = {0u, 0u}, f1[2] = {0u, 0u};
      uint32_t f2[2] = {0u, 0u}, f3[2] = {0u, 0u}, f4[2] = {0u, 0u}, f5[2] = {0u, 0u};
      uint32_t k0;
      {
        uint32_t b0[4], b1[4], b2[4], b3[4], c0[4], c1[4], c2[4], c3[4];
        ldsm4t(u_o0 + l16, b0); ldsm4t(u_o0 + 512 + l16, b1);
        BB_FENCE(1);
        hhmma(hf, T[0], b0[0], b0[1]); hhmma(hg, T[1], b0[2], b0[3]);
        hhmma(f0, T[4], b0[0], b0[1]); hhmma(f1, T[5], b0[2], b0[3]);
        ldsm4t(u_o0 + 1024 + l16, b2);
        hhmma(hf, T[2], b1[0], b1[1]); hhmma(hg, T[3], b1[2], b1[3]);
        ldsm4t(u_o0 + 1536 + l16, b3); ldsm4t(u_o1 + l16, c0);
        hhmma(f0, T[6], b1[0], b1[1]); hhmma(f1, T[7], b1[2], b1[3]);
        ldsm4t(u_o1 + 512 + l16, c1); ldsm4t(u_o1 + 1024 + l16, c2); ldsm4t(u_o1 + 1536 + l16, c3);
        AFENCE(7);
        hhmma(hf, R[0], b2[0], b2[1]); hhmma(hg, R[1], b2[2], b2[3]);
        hhmma(f0, R[4], b2[0], b2[1]); hhmma(f1, R[5], b2[2], b2[3]);
        hhmma(hf, R[2], b3[0], b3[1]); hhmma(hg, R[3], b3[2], b3[3]);
        hhmma(f2, R[8], c0[0], c0[1]); hhmma(f3, R[9], c0[2], c0[3]);
        hhmma(f0, R[6], b3[0], b3[1]); hhmma(f1, R[7], b3[2], b3[3]);
        hhmma(f4, R[10], c1[0], c1[1]);
        {
          const uint32_t x0 = hadd2u(hf[0], hg[0]), x1 = hadd2u(hf[1], hg[1]);
          k0 = (a & 1) ? x1 : x0;
          sts32(sb + SM_PAIR + (a ^ 1) * 128 + (l16 >> 2), (a & 1) ? x0 : x1);
        }
        hhmma(f5, R[11], c1[2], c1[3]);
        hhmma(f2, R[12], c2[0], c2[1]); hhmma(f3, R[13], c2[2], c2[3]);
        hhmma(f4, R[14], c3[0], c3[1]); hhmma(f5, R[15], c3[2], c3[3]);
      }
      bar_sync(8, 192);
      const uint32_t io = lds32(sb + SM_LI + (a & 1) * 128 + ((l16 >> 2) & 12)), jo = lds32(sb + SM_LI + ((a & 1) ^ 1) * 128 + ((l16 >> 2) & 12));
      const uint32_t y0 = lds32(sb + SM_PAIR + a * 128 + (l16 >> 2));
      unsigned char* wp = exu + (s & 3) * EX_BUF + l16;
      BB_FENCE(11);
      {
        const uint32_t e2 = hfma2u(y0, jo, hmul2u(k0, io));
        const uint32_t e0 = hfma2u(hadd2u(hadd2u(f2[0], f3[0]), hadd2u(f4[0], f5[0])), jo, hmul2u(hadd2u(f0[0], f1[0]), io));
        const uint32_t e1 = hfma2u(hadd2u(hadd2u(f2[1], f3[1]), hadd2u(f4[1], f5[1])), jo, hmul2u(hadd2u(f0[1], f1[1]), io));
        asm volatile("red.relaxed.gpu.global.add.noftz.v4.f16x2 [%0], {%1,%2,%3,%4};"
                     ::"l"(wp), "r"(e0), "r"(e1), "r"(e2), "r"(0x3c00u) : "memory");
      }
      bar_arrive(7, 384);
      const uint32_t tw = clk32();
      PROF_W(8, 9);
      PROF_W(warp, 28 + a);
      uint32_t v[4];
      int it = 0;
      const uint32_t scr = sb + SM_SC2 + a * 2560 + (uint32_t)__shfl_xor_sync(0xffffffffu, l16, 0);
#define POLL() asm volatile("ld.relaxed.gpu.global.v4.b32 {%0,%1,%2,%3}, [%4];" : "=r"(v[0]), "=r"(v[1]), "=r"(v[2]), "=r"(v[3]) : "l"(wp) : "memory")
#define POK() __all_sync(0xffffffffu, v[3] == 0x4c00u)
      while (clk32() - tw < POLL_DELAY) {}
      POLL();
#pragma unroll
      for (int i = 1; i < NPOLL; i++) {
        while (clk32() - tw < POLL_DELAY + i * POLL_GAP) {}
        cp_async16(scr + (i - 1) * 512, wp);
        asm volatile("cp.async.commit_group;" ::: "memory");
      }
      BB_FENCE(13);
#define PSTEP(i) if (NPOLL > i) { if (POK()) goto pdone; it = i; asm volatile("cp.async.wait_group %0;" ::"n"(NPOLL > i ? NPOLL - 1 - i : 0) : "memory"); lds128(scr + (i - 1) * 512, v); }
      PSTEP(1) PSTEP(2) PSTEP(3) PSTEP(4) PSTEP(5)
#undef PSTEP
      while (!POK()) {
        if (++it > 20000) { *(volatile unsigned int*)&g_err = 2; break; }
        POLL();
      }
pdone:
#undef POLL
#undef POK
      PROF_W(8, 10);
      PROF_W(warp, 16 + a);
      send_unit(0, f16_to_bf16(v[0]));
      send_unit(1, f16_to_bf16(v[1]));
      if (has3) send_unit(2, f16_to_bf16(v[2]));
      if ((int)(l16 >> 5) == cl)
        asm volatile("st.relaxed.gpu.global.v4.b32 [%0], {%1,%1,%1,%1};" ::"l"(exu + ((s + 2) & 3) * EX_BUF + l16), "r"(0u) : "memory");
    }
    cp_async_wait_all();
    __syncwarp();
    cluster_sync();
  } else {
    reg_dec<48>();
    if (tid == 480) {
#pragma unroll 1
      for (int i = WL_AHEAD; i < 8; i++) { mbar_wait(BAR(B_WL + i - WL_AHEAD), 0); wload(i); }
      mbar_arrive_tx(BAR(B_WO), 49152);
#pragma unroll 1
      for (int i = 0; i < 4; i++) {
        mbar_wait(BAR(B_WL + min(7, 8 - WL_AHEAD + i)), 0);
        tma2d(sb + SM_WO + i * 8192, &wm.o64, cb * 8, cl * 256 + i * 64, BAR(B_WO));
        tma2d(sb + SM_WO + 32768 + i * 4096, &wm.o32, cb * 8 + 64, cl * 256 + i * 64, BAR(B_WO));
      }
    }
    __syncwarp();
    cluster_wait(); cluster_arrive_rlx();
    if (tid == 384) {
      mbar_arrive_tx(BAR(B_XAF), 16384);
      mbar_arrive_tx(BAR(B_XNF), 16384);
      mbar_arrive_tx(BAR(B_XN1), 32768);
      if (rank == 0) {
        poll_ge(&g_ln0, lds32(sb + SM_EP) * 64);
        fence_async_all();
#pragma unroll 1
        for (int kc = 0; kc < 8; kc++)
          bulk_g2s_mc(sb + SM_XN + kc * 4096, g_xn + (size_t)kc * S_TOK * 128, 4096, BAR(kc < 4 ? B_XAF : B_XNF), 0x3f);
      }
    }
    __syncwarp();
    cluster_wait();
    if (tid == 384 && rank == 0) {
#pragma unroll 1
      for (int kc = 0; kc < 8; kc++)
        bulk_g2s_mc(sb + SM_V + 32768 + kc * 4096, g_xn + ((size_t)kc * S_TOK + 32) * 128, 4096, BAR(B_XN1), 0x3f);
    }
    if (warp == 15) {
      if (lane == 0) {
        for (int h = 4; h < 2 * NSEG; h++) {
          const int g = h >> 1;
          if (rank == 0 && (h == 4 || h == 8)) {
            poll_ge(h == 4 ? &g_ln1 : &g_lncnt, lds32(sb + SM_EP) * (h == 4 ? 64 : NHELP));
            fence_async_all();
          }
          const uint32_t bf = BAR(h & 1 ? B_XNF : B_XAF);
          mbar_wait(bf, g & 1);
          mbar_arrive_tx(bf, 16384);
          if (rank == 0) {
            mbar_wait(BAR(h & 1 ? B_XNE : B_XAE), g & 1);
#pragma unroll 1
            for (int kc = (h & 1) * 4; kc < (h & 1) * 4 + 4; kc++)
              bulk_g2s_mc(sb + SM_XN + kc * 4096, g_xn + ((size_t)kc * S_TOK + g * 32) * 128, 4096, bf, 0x3f);
          }
        }
      }
    } else if (warp == 12) {
      if (lane == 0) {
        for (int g = 0; g < NSEG; g++) {
          const int slot = g & 3, slot8 = g & 7;
          mbar_arrive_tx(BAR(B_VF + (g % NVST)), 16384);
          mbar_wait(BAR(B_STF), g & 1);
          if (g >= 2) mbar_hint(BAR(B_MEM + H2W), (g - 1) & 1);
          fence_async_smem();
          unsigned char* vdst = g_v + (size_t)(slot * NCL + cl) * 16384 + (hl * 16 + v0 * 2) * 512;
          const uint32_t src = sb + SM_KX + (g % 3) * KX_SLOT;
          bulk_s2g(vdst, src + 2 * nqk * 1024, nv * 1024);
          bulk_s2g(g_q + (size_t)(slot8 * NH + head) * 8192 + qk0 * 1024, src, nqk * 1024);
          bulk_s2g(g_k + (size_t)(slot8 * NH + head) * 8192 + qk0 * 1024, src + nqk * 1024, nqk * 1024);
          bulk_commit();
          bulk_wait_read();
          mbar_arrive(BAR(B_STE));
          bulk_wait_all();
          fence_async_all();
          if (g >= NVST) mbar_wait(BAR(B_VE + (g % NVST)), ((g / NVST) - 1) & 1);
          if (g >= 2) mbar_hint(BAR(B_SC), (g - 1) & 1);
          bulk_g2s_mc(sb + SM_V + (g % NVST) * 16384 + (hl * 16 + v0 * 2) * 512, vdst, nv * 1024, BAR(B_VF + (g % NVST)), 0x3f);
          mbar_arrive_remote_rel(mapa(BAR(B_QKR + ((g / 3) & 1)), hl * 3 + (g % 3)));
        }
      }
    } else {
      const int rt = warp - 13;
      int n = 0;
      if (rt == 0 && lane == 0) mbar_arrive_tx(BAR(B_KMF), 2048);
      mbar_wait(BAR(B_P3), 0);
      for (int g = jj; g < NSEG; g += 3, n++) {
        if (rt == 0 && lane == 0) {
          if (g + 3 < NSEG) mbar_arrive_tx(BAR(B_KMF + ((n + 1) & 1)), 2048);
          mbar_wait_acq(BAR(B_QKR + (n & 1)), (n >> 1) & 1);
          fence_async_all();
          mbar_arrive_tx(BAR(B_ATF), 16384);
          bulk_g2s(sb + SM_ATQ, g_q + (size_t)((g & 7) * NH + head) * 8192, 8192, BAR(B_ATF));
          bulk_g2s(sb + SM_ATK, g_k + (size_t)((g & 7) * NH + head) * 8192, 8192, BAR(B_ATF));
        }
        __syncwarp();
#define GA(i) if (rt == 1 && lane == 0 && g >= 61) GT(blockIdx.x, 72 + (i))
        GA(0);
        mbar_wait(BAR(B_ATF), n & 1);
        GA(1);
        float sc[5][4];
#pragma unroll
        for (int t = 0; t < 5; t++) sc[t][0] = sc[t][1] = sc[t][2] = sc[t][3] = 0.f;
        {
          const uint32_t qa = sb + SM_ATQ + (lane >> 4) * 512 + (2 * rt + ((lane >> 3) & 1)) * 128 + (lane & 7) * 16;
          const uint32_t ka = sb + SM_ATK + lane * 16;
#pragma unroll 1
          for (int ks = 0; ks < ATTN; ks++) {
            uint32_t q[4], b0[4], b1[4];
            ldsm4(qa + ks * 1024, q);
            ldsm4(ka + ks * 1024, b0); ldsm4(ka + ks * 1024 + 512, b1);
            mma16816(sc[0], q, b0[0], b1[0]);
            mma16816(sc[1], q, b0[1], b1[1]);
            if (rt) { mma16816(sc[2], q, b0[2], b1[2]); mma16816(sc[3], q, b0[3], b1[3]); }
          }
          const uint32_t kma = sb + SM_KMA + (n & 1) * 2048 + lane * 16;
          float s2[4] = {0.f, 0.f, 0.f, 0.f};
          mbar_wait(BAR(B_KMF + (n & 1)), (n >> 1) & 1);
          GA(2);
#pragma unroll 1
          for (int ks = 0; ks < ATTN; ks += 2) {
            uint32_t q0[4], q1[4], bm[4];
            ldsm4(qa + ks * 1024, q0); ldsm4t(kma + ks * 256, bm); ldsm4(qa + ks * 1024 + 1024, q1);
            mma16816(sc[4], q0, bm[0], bm[1]);
            mma16816(s2, q1, bm[2], bm[3]);
          }
#pragma unroll
          for (int i = 0; i < 4; i++) sc[4][i] += s2[i];
        }
        GA(3);
        const int r0 = 16 * rt + (lane >> 2), kq = (lane & 3) * 2;
        float m0 = fmaxf(sc[4][0], sc[4][1]), m1 = fmaxf(sc[4][2], sc[4][3]);
#pragma unroll
        for (int t = 0; t < 4; t++) {
          const int k0 = 8 * t + kq;
          if (k0 > r0) sc[t][0] = -INFINITY;
          if (k0 + 1 > r0) sc[t][1] = -INFINITY;
          if (k0 > r0 + 8) sc[t][2] = -INFINITY;
          if (k0 + 1 > r0 + 8) sc[t][3] = -INFINITY;
          m0 = fmaxf(m0, fmaxf(sc[t][0], sc[t][1]));
          m1 = fmaxf(m1, fmaxf(sc[t][2], sc[t][3]));
        }
        m0 = fmaxf(m0, __shfl_xor_sync(0xffffffffu, m0, 1)); m0 = fmaxf(m0, __shfl_xor_sync(0xffffffffu, m0, 2));
        m1 = fmaxf(m1, __shfl_xor_sync(0xffffffffu, m1, 1)); m1 = fmaxf(m1, __shfl_xor_sync(0xffffffffu, m1, 2));
        const float n0 = -m0 * SC_LOG2E, n1 = -m1 * SC_LOG2E;
        uint32_t p[5][2];
        float l0 = 0.f, l1 = 0.f;
#pragma unroll
        for (int t = 0; t < 5; t++) {
          p[t][0] = pack_f16(ex2(fmaf(sc[t][0], SC_LOG2E, n0)), ex2(fmaf(sc[t][1], SC_LOG2E, n0)));
          p[t][1] = pack_f16(ex2(fmaf(sc[t][2], SC_LOG2E, n1)), ex2(fmaf(sc[t][3], SC_LOG2E, n1)));
          const float2 e0 = h2f2(p[t][0]), e1 = h2f2(p[t][1]);
          l0 += e0.x + e0.y;
          l1 += e1.x + e1.y;
        }
        l0 += __shfl_xor_sync(0xffffffffu, l0, 1); l0 += __shfl_xor_sync(0xffffffffu, l0, 2);
        l1 += __shfl_xor_sync(0xffffffffu, l1, 1); l1 += __shfl_xor_sync(0xffffffffu, l1, 2);
        const float i0 = 1.f / l0, i1 = 1.f / l1;
        GA(4);
        mbar_wait(BAR(B_VF + (g % NVST)), (g / NVST) & 1);
        if (g == NSEG - 1) {
          const uint32_t a_p = sb + SM_SCR + rt * 1536 + lane * 16;
          sts128(a_p, p[0][0], p[0][1], p[1][0], p[1][1]); sts128(a_p + 512, p[2][0], p[2][1], p[3][0], p[3][1]);
          sts128(a_p + 1024, p[4][0], p[4][1], __float_as_uint(i0), __float_as_uint(i1));
          bar_arrive(10, 320);
          break;
        }
        mbar_wait(BAR(B_VM + (g & 3)), (g >> 2) & 1);
        GA(5);
#pragma unroll 1
        for (int np = 0; np < ATTN; np++) pv_step(p, i0, i1, g, rt, np);
        GA(6);
        fence_async_smem();
        __syncwarp();
        if (lane < CLS) mbar_arrive_remote(mapa(BAR(B_VE + (g % NVST)), lane));
        if (lane == 0) ox_publish(g, rt);
        bar_sync(6, 64);
      }
    }
    __syncwarp();
    cluster_sync();
  }
}

#define HELP_DELAY 3000
constexpr int G_STAGES = 4, G_STAGE_BYTES = 49152;
constexpr int G_SM_HST = G_STAGES * G_STAGE_BYTES;
constexpr int G_SM_BAR = G_SM_HST + 32768;
constexpr int G_SM_FIN = G_SM_BAR + 512;
constexpr int G_SM_END = G_SM_FIN + 1024;
constexpr int G_SM_RING = 131072;
static_assert(G_SM_RING + 3 * 32768 <= G_SM_BAR && G_SM_END <= 232448, "smem");
__device__ __forceinline__ void wgmma_ss_n256(float* c, uint64_t da, uint64_t db, int acc) {
  asm volatile("{\n.reg .pred p;\nsetp.ne.b32 p, %130, 0;\n"
    "wgmma.mma_async.sync.aligned.m64n256k16.f32.bf16.bf16 {"
    "%0,%1,%2,%3,%4,%5,%6,%7,%8,%9,%10,%11,%12,%13,%14,%15,%16,%17,%18,%19,%20,%21,%22,%23,%24,%25,%26,%27,%28,%29,%30,%31,"
    "%32,%33,%34,%35,%36,%37,%38,%39,%40,%41,%42,%43,%44,%45,%46,%47,%48,%49,%50,%51,%52,%53,%54,%55,%56,%57,%58,%59,%60,%61,%62,%63,"
    "%64,%65,%66,%67,%68,%69,%70,%71,%72,%73,%74,%75,%76,%77,%78,%79,%80,%81,%82,%83,%84,%85,%86,%87,%88,%89,%90,%91,%92,%93,%94,%95,"
    "%96,%97,%98,%99,%100,%101,%102,%103,%104,%105,%106,%107,%108,%109,%110,%111,%112,%113,%114,%115,%116,%117,%118,%119,%120,%121,%122,%123,%124,%125,%126,%127"
    "}, %128, %129, p, 1, 1, 0, 1;\n}"
    : "+f"(c[0]), "+f"(c[1]), "+f"(c[2]), "+f"(c[3]), "+f"(c[4]), "+f"(c[5]), "+f"(c[6]), "+f"(c[7]),
      "+f"(c[8]), "+f"(c[9]), "+f"(c[10]), "+f"(c[11]), "+f"(c[12]), "+f"(c[13]), "+f"(c[14]), "+f"(c[15]),
      "+f"(c[16]), "+f"(c[17]), "+f"(c[18]), "+f"(c[19]), "+f"(c[20]), "+f"(c[21]), "+f"(c[22]), "+f"(c[23]),
      "+f"(c[24]), "+f"(c[25]), "+f"(c[26]), "+f"(c[27]), "+f"(c[28]), "+f"(c[29]), "+f"(c[30]), "+f"(c[31]),
      "+f"(c[32]), "+f"(c[33]), "+f"(c[34]), "+f"(c[35]), "+f"(c[36]), "+f"(c[37]), "+f"(c[38]), "+f"(c[39]),
      "+f"(c[40]), "+f"(c[41]), "+f"(c[42]), "+f"(c[43]), "+f"(c[44]), "+f"(c[45]), "+f"(c[46]), "+f"(c[47]),
      "+f"(c[48]), "+f"(c[49]), "+f"(c[50]), "+f"(c[51]), "+f"(c[52]), "+f"(c[53]), "+f"(c[54]), "+f"(c[55]),
      "+f"(c[56]), "+f"(c[57]), "+f"(c[58]), "+f"(c[59]), "+f"(c[60]), "+f"(c[61]), "+f"(c[62]), "+f"(c[63]),
      "+f"(c[64]), "+f"(c[65]), "+f"(c[66]), "+f"(c[67]), "+f"(c[68]), "+f"(c[69]), "+f"(c[70]), "+f"(c[71]),
      "+f"(c[72]), "+f"(c[73]), "+f"(c[74]), "+f"(c[75]), "+f"(c[76]), "+f"(c[77]), "+f"(c[78]), "+f"(c[79]),
      "+f"(c[80]), "+f"(c[81]), "+f"(c[82]), "+f"(c[83]), "+f"(c[84]), "+f"(c[85]), "+f"(c[86]), "+f"(c[87]),
      "+f"(c[88]), "+f"(c[89]), "+f"(c[90]), "+f"(c[91]), "+f"(c[92]), "+f"(c[93]), "+f"(c[94]), "+f"(c[95]),
      "+f"(c[96]), "+f"(c[97]), "+f"(c[98]), "+f"(c[99]), "+f"(c[100]), "+f"(c[101]), "+f"(c[102]), "+f"(c[103]),
      "+f"(c[104]), "+f"(c[105]), "+f"(c[106]), "+f"(c[107]), "+f"(c[108]), "+f"(c[109]), "+f"(c[110]), "+f"(c[111]),
      "+f"(c[112]), "+f"(c[113]), "+f"(c[114]), "+f"(c[115]), "+f"(c[116]), "+f"(c[117]), "+f"(c[118]), "+f"(c[119]),
      "+f"(c[120]), "+f"(c[121]), "+f"(c[122]), "+f"(c[123]), "+f"(c[124]), "+f"(c[125]), "+f"(c[126]), "+f"(c[127])
    : "l"(da), "l"(db), "r"(acc));
}

__global__ void __launch_bounds__(384, 1)
k_help(const __grid_constant__ CUtensorMap tmG, const __grid_constant__ CUtensorMap tmU, const __grid_constant__ CUtensorMap tmD,
       const __grid_constant__ CUtensorMap tmO, const __nv_bfloat16* __restrict__ x, __nv_bfloat16* __restrict__ out) {
  extern __shared__ __align__(1024) unsigned char smem[];
  const uint32_t sb = smem_u32(smem);
  const int tid = threadIdx.x, lane = tid & 31, warp = tid >> 5;
  const int j = blockIdx.x, ks8 = j >> 2, cg = j & 3;
  const uint32_t fullb = sb + G_SM_BAR, emptyb = fullb + 8 * G_STAGES, wbar = emptyb + 8 * G_STAGES;
  const uint32_t full2 = wbar + 8, empty2 = full2 + 8 * 12, done2 = empty2 + 8 * 3;
  if (tid == 0) GT(100 + j, 0);
  {
    uint4 v[5][2];
#pragma unroll
    for (int i = 0; i < 5; i++) {
      const int row = i * (NHELP * 12) + j * 12 + warp;
      if (row < S_TOK) {
        const uint4* src = reinterpret_cast<const uint4*>(x + (size_t)row * DM);
        v[i][0] = src[lane]; v[i][1] = src[lane + 32];
      }
    }
    if (tid == 32) sts32(done2 + 8, atomicAdd(&g_done, 1u) / NCTA + 1);
#pragma unroll
    for (int i = 0; i < 5; i++) {
      const int row = i * (NHELP * 12) + j * 12 + warp;
      if (row < S_TOK) {
        ln_row(v[i][0], v[i][1]);
        unsigned char* d = g_xn + ((size_t)(lane >> 3) * S_TOK + row) * 128 + (((lane & 7) ^ (row & 7)) << 4);
        *reinterpret_cast<uint4*>(d) = v[i][0];
        *reinterpret_cast<uint4*>(d + (size_t)4 * S_TOK * 128) = v[i][1];
        if (i == 0 && row < 128) { __syncwarp(); if (lane == 0) red_release(row < 64 ? &g_ln0 : &g_ln1); }
      }
    }
  }
  if (tid == 0) {
    for (int i = 0; i < G_STAGES; i++) { mbar_init(fullb + 8 * i, 1); mbar_init(emptyb + 8 * i, 2); }
    mbar_init(wbar, 1);
    for (int i = 0; i < 12; i++) mbar_init(full2 + 8 * i, 1);
    for (int i = 0; i < 3; i++) mbar_init(empty2 + 8 * i, 2);
    sts32(done2, 0); sts32(done2 + 4, 0);
    asm volatile("fence.mbarrier_init.release.cluster;" ::: "memory");
  }
  __syncthreads();
  if (tid == 64) { GT(200 + j, 3); red_release(&g_lncnt); GT(100 + j, 7); }
  const uint32_t ep = lds32(done2 + 8);
  const int nup = (176 - j + NHELP - 1) / NHELP;
  const int nit = nup + (j < 32 ? 1 : 0);
  if (warp < 4) {
    reg_dec<88>();
    if (tid == 0) {
      int st = 0, ph = 0;
      poll_ge(&g_lncnt, ep * NHELP);
      fence_async_all();
      { const uint32_t t0 = clk32(); while (clk32() - t0 < HELP_DELAY) {} }
      for (int n = 0; n < nit; n++) {
        const bool up = n < nup;
        const int item = j + n * NHELP;
        const int blk = up ? item / 11 : j >> 1, nt = up ? item % 11 : j & 1;
        const int nk = up ? 8 : HCH;
        if (!up) { GT(100 + j, 1); poll_ge(&g_hcnt[blk], ep * 22); fence_async_all(); GT(100 + j, 2); }
        for (int kc = 0; kc < nk; kc++) {
          mbar_wait(emptyb + 8 * st, ph ^ 1);
          const uint32_t sa = sb + st * G_STAGE_BYTES, bar = fullb + 8 * st;
          mbar_arrive_tx(bar, G_STAGE_BYTES);
          if (up) {
            bulk_g2s(sa, g_xn + ((size_t)kc * S_TOK + blk * 128) * 128, 16384, bar);
            tma2d(sa + 16384, &tmG, nt * 128, kc * 64, bar);
            tma2d(sa + 16384 + 8192, &tmG, nt * 128 + 64, kc * 64, bar);
            tma2d(sa + 16384 + 16384, &tmU, nt * 128, kc * 64, bar);
            tma2d(sa + 16384 + 24576, &tmU, nt * 128 + 64, kc * 64, bar);
          } else {
            bulk_g2s(sa, g_h + ((size_t)kc * S_TOK + blk * 128) * 128, 16384, bar);
#pragma unroll
            for (int i = 0; i < 4; i++) tma2d(sa + 16384 + i * 8192, &tmD, nt * 256 + i * 64, kc * 64, bar);
          }
          if (++st == G_STAGES) { st = 0; ph ^= 1; }
        }
      }
      if (j < 32) {
        for (int i = 0; i < G_STAGES; i++) {
          mbar_wait(emptyb + 8 * st, ph ^ 1);
          if (++st == G_STAGES) { st = 0; ph ^= 1; }
        }
        GT(100 + j, 3);
        mbar_arrive_tx(wbar, 131072);
        for (int i = 0; i < 16; i++) tma2d(sb + i * 8192, &tmO, cg * 128 + (i >> 3) * 64, ks8 * 512 + (i & 7) * 64, wbar);
        int slot = 0, ready = 0; ph = 0;
        for (int g = 0; g < NSEG; g++) {
          mbar_wait(empty2 + 8 * slot, ph ^ 1);
          if ((g & 3) == 0) poll_ge(&g_dcnt[(g >> 2) * 2 + (cg >> 1)], ep * 3);
#pragma unroll
          for (int q = 0; q < 4; q++) mbar_arrive_tx(full2 + 8 * (slot * 4 + q), 8192);
          if (g >= ready) {
            for (int it = 0; it < 30000; it++) {
              uint32_t r[4];
              asm volatile("ld.acquire.gpu.global.v4.u32 {%0,%1,%2,%3}, [%4];" : "=r"(r[0]), "=r"(r[1]), "=r"(r[2]), "=r"(r[3])
                           : "l"(&g_cnt[ks8 * NSEG + (g & ~3)]) : "memory");
              ready = g;
#pragma unroll
              for (int i = 0; i < 4; i++) if (ready == (g & ~3) + i && (int)(r[i] - ep * 8) >= 0) ready++;
              if (ready > g) break;
            }
            fence_async_all();
          }
          if (g == 63) GT(100 + j, 4);
          const unsigned char* src = g_ox + ((size_t)(ks8 * 8) * S_TOK + g * 32) * 128;
#pragma unroll
          for (int kc = 0; kc < 8; kc++)
            bulk_g2s(sb + G_SM_RING + slot * 32768 + kc * 4096, src + (size_t)kc * S_TOK * 128, 4096, full2 + 8 * (slot * 4 + (kc >> 1)));
          if (++slot == 3) { slot = 0; ph ^= 1; }
        }
      }
    } else if (warp == 1 && j < 32) {
      {
        unsigned char* dst = g_acc + (size_t)((j >> 1) * 4 * 32 + (j & 1) * 16) * 1536 + lane * 16;
#pragma unroll 1
        for (int g = 0; g < 4; g++)
#pragma unroll 8
          for (int i = 0; i < 48; i++) *reinterpret_cast<uint4*>(dst + g * 32 * 1536 + i * 512) = make_uint4(0u, 0u, 0u, 0u);
        __syncwarp();
        if (lane == 0) red_release(&g_dcnt[j]);
      }
      const int col = cg * 128 + ks8 * 16;
      const uint32_t fs = sb + G_SM_FIN;
#pragma unroll 1
      for (int g = 0; g < NSEG; g++) {
        if ((g & 3) == 0) poll_ge(&g_dcnt[(g >> 2) * 2 + (cg >> 1)], ep * 3);
        float4 f[4];
        const float4* fp = reinterpret_cast<const float4*>(g_ffn + (size_t)(g * 32 + lane) * DM + col);
#pragma unroll
        for (int i = 0; i < 4; i++) f[i] = __ldcg(fp + i);
        for (int it = 0; it < 400000; it++) {
          uint32_t d0, d1;
          asm volatile("ld.volatile.shared.v2.b32 {%0,%1}, [%2];" : "=r"(d0), "=r"(d1) : "r"(done2) : "memory");
          if ((int)min(d0, d1) > g) break;
          __nanosleep(20);
        }
        const unsigned char* ap = g_acc + (size_t)(g * 32 + cg * 8 + ks8) * 1536 + lane * 16;
        uint32_t v[3][4];
        for (int it = 0;; it++) {
#pragma unroll
          for (int i = 0; i < 3; i++)
            asm volatile("ld.relaxed.gpu.global.v4.b32 {%0,%1,%2,%3}, [%4];" : "=r"(v[i][0]), "=r"(v[i][1]), "=r"(v[i][2]), "=r"(v[i][3]) : "l"(ap + i * 512) : "memory");
          if (__all_sync(0xffffffffu, v[0][3] == 0x4800u && v[1][3] == 0x4800u && v[2][3] == 0x4800u)) break;
          if (it > 30000) { *(volatile unsigned int*)&g_err = 4; break; }
        }
        const uint32_t ra = fs + (lane >> 3) * 256 + (lane & 7) * 32;
        stsm4t(ra, v[0][0], v[0][1], v[0][2], v[1][0]);
        stsm4t(ra + 16, v[1][1], v[1][2], v[2][0], v[2][1]);
        __syncwarp();
        uint32_t t[8];
        lds128(fs + lane * 32, t); lds128(fs + lane * 32 + 16, t + 4);
        __syncwarp();
        uint32_t o[8];
#pragma unroll
        for (int i = 0; i < 4; i++) {
          const float2 a = __half22float2(*reinterpret_cast<__half2*>(&t[2 * i])), b = __half22float2(*reinterpret_cast<__half2*>(&t[2 * i + 1]));
          o[2 * i] = pack_bf16(f[i].x + a.x, f[i].y + a.y);
          o[2 * i + 1] = pack_bf16(f[i].z + b.x, f[i].w + b.y);
        }
        uint4* op = reinterpret_cast<uint4*>(out + (size_t)(g * 32 + lane) * DM + col);
        op[0] = make_uint4(o[0], o[1], o[2], o[3]);
        op[1] = make_uint4(o[4], o[5], o[6], o[7]);
        if (lane == 0) GT(100 + j, 8 + g);
      }
      pdl_wait();
      if (lane == 0) GT(100 + j, 6);
    }
  } else {
    reg_inc<208>();
    const int wg = (warp >> 2) - 1;
    const bool lead = (tid & 127) == 0;
    {
      float c[128];
      int st = 0, ph = 0;
      int pend = -1;
      for (int n = 0; n < nit; n++) {
        const bool up = n < nup;
        const int item = j + n * NHELP;
        const int blk = up ? item / 11 : j >> 1, nt = up ? item % 11 : j & 1;
        const int nk = up ? 8 : HCH;
        if (!up && lead) { bulk_wait_all(); fence_async_all(); red_release(&g_hcnt[pend]); }
        int prev = -1;
        for (int kc = 0; kc < nk; kc++) {
          mbar_wait(fullb + 8 * st, ph);
          const uint32_t sa = sb + st * G_STAGE_BYTES;
          wg_fence();
#pragma unroll
          for (int ks = 0; ks < 4; ks++)
            wgmma_ss_n256(c, mkdesc(sa + wg * 8192 + ks * 32, 16, 1024), mkdesc(sa + 16384 + ks * 2048, 8192, 1024), kc | ks);
          wg_commit();
          if (prev >= 0) { wg_wait<1>(); if (lead) mbar_arrive(emptyb + 8 * prev); }
          prev = st;
          if (++st == G_STAGES) { st = 0; ph ^= 1; }
        }
        wg_wait<0>();
        if (lead) mbar_arrive(emptyb + 8 * prev);
        const int wr = (warp & 3) * 16;
        if (up) {
          const uint32_t stg = sb + G_SM_HST + wg * 16384;
          if (lead && pend >= 0) { bulk_wait_all(); fence_async_all(); red_release(&g_hcnt[pend]); }
          pend = blk;
          bar_sync(1 + wg, 128);
          const int row = wr + (lane & 7) + ((lane >> 3) & 1) * 8;
#pragma unroll
          for (int np = 0; np < 8; np++) {
            uint32_t r[4];
#pragma unroll
            for (int t = 0; t < 2; t++) {
              const int i = (2 * np + t) * 4;
              r[2 * t] = pack_bf16(bfr(c[i]) * bfr(c[64 + i]), bfr(c[i + 1]) * bfr(c[64 + i + 1]));
              r[2 * t + 1] = pack_bf16(bfr(c[i + 2]) * bfr(c[64 + i + 2]), bfr(c[i + 3]) * bfr(c[64 + i + 3]));
            }
            const int c16 = 2 * np + (lane >> 4);
            stsm4(stg + (c16 >> 3) * 8192 + row * 128 + (((c16 & 7) ^ (row & 7)) << 4), r[0], r[1], r[2], r[3]);
          }
          fence_async_smem();
          bar_sync(1 + wg, 128);
          if (lead) {
            unsigned char* dst = g_h + ((size_t)(nt * 2) * S_TOK + blk * 128 + wg * 64) * 128;
            bulk_s2g(dst, stg, 8192);
            bulk_s2g(dst + (size_t)S_TOK * 128, stg + 8192, 8192);
            bulk_commit();
            if (n == nit - 1) { bulk_wait_all(); fence_async_all(); red_release(&g_hcnt[blk]); }
          }
        } else {
          const int r0 = blk * 128 + wg * 64 + wr + (lane >> 2);
          const int c0 = nt * 256 + (lane & 3) * 2;
#pragma unroll
          for (int i = 0; i < 32; i++) {
            const size_t o0 = (size_t)r0 * DM + c0 + i * 8, o1 = o0 + 8 * DM;
            const uint32_t x0 = *reinterpret_cast<const uint32_t*>(x + o0), x1 = *reinterpret_cast<const uint32_t*>(x + o1);
            *reinterpret_cast<float2*>(g_ffn + o0) = make_float2(bf_lo(x0) + c[4 * i], bf_hi(x0) + c[4 * i + 1]);
            *reinterpret_cast<float2*>(g_ffn + o1) = make_float2(bf_lo(x1) + c[4 * i + 2], bf_hi(x1) + c[4 * i + 3]);
          }
          bar_sync(1 + wg, 128);
          if (lead) red_release(&g_dcnt[j]);
        }
      }
    }
    if (j < 32) {
      uint32_t W[32][4];
      mbar_wait(wbar, 0);
      {
        const int kr = (lane & 7) + ((lane >> 4) << 3), ch = (warp & 3) * 2 + ((lane >> 3) & 1);
        const uint32_t a0 = sb + wg * 65536 + kr * 128 + ((ch ^ (kr & 7)) << 4);
#pragma unroll
        for (int ks = 0; ks < 32; ks++) ldsm4t(a0 + ks * 2048, W[ks]);
      }
      unsigned char* ap = g_acc + (size_t)(cg * 8 + warp - 4) * 1536 + lane * 16;
      int slot = 0, ph = 0;
#pragma unroll 1
      for (int g = 0; g < NSEG; g++) {
        float c[16];
        const uint32_t dlo = (((sb + G_SM_RING + slot * 32768) & 0x3FFFF) >> 4) | (1u << 16);
#pragma unroll
        for (int q = 0; q < 4; q++) {
          mbar_wait(full2 + 8 * (slot * 4 + q), ph);
          if (q == 0) wg_fence();
#pragma unroll
          for (int ks = q * 8; ks < q * 8 + 8; ks++)
            wgmma_rs_n32(c, W[ks], ((uint64_t)0x40000040u << 32) | (uint64_t)(dlo + (ks >> 2) * 256 + (ks & 3) * 2), ks);
        }
        wg_commit();
        wg_wait<0>();
        if (lead) mbar_arrive(empty2 + 8 * slot);
        uint32_t w[9];
#pragma unroll
        for (int nt = 0; nt < 4; nt++) { w[nt] = pack_f16(c[4 * nt], c[4 * nt + 1]); w[4 + nt] = pack_f16(c[4 * nt + 2], c[4 * nt + 3]); }
        w[8] = 0;
#pragma unroll
        for (int i = 0; i < 3; i++)
          asm volatile("red.relaxed.gpu.global.add.noftz.v4.f16x2 [%0], {%1,%2,%3,%4};"
                       ::"l"(ap + i * 512), "r"(w[3 * i]), "r"(w[3 * i + 1]), "r"(w[3 * i + 2]), "r"(0x3c00u) : "memory");
        if (lead) asm volatile("st.volatile.shared.b32 [%0], %1;" ::"r"(done2 + wg * 4), "r"(g + 1) : "memory");
        if (lead && wg == 0 && g == 63) GT(100 + j, 5);
        ap += 32 * 1536;
        if (++slot == 3) { slot = 0; ph ^= 1; }
      }
    }
  }
}

typedef CUresult (*EncodeFn)(CUtensorMap*, CUtensorMapDataType, cuuint32_t, void*, const cuuint64_t*, const cuuint64_t*,
                             const cuuint32_t*, const cuuint32_t*, CUtensorMapInterleave, CUtensorMapSwizzle,
                             CUtensorMapL2promotion, CUtensorMapFloatOOBfill);

void make_map(EncodeFn fn, CUtensorMap* m, const void* p, int rows, int cols, int bc = 64, int br = 64) {
  cuuint64_t dims[2] = {(cuuint64_t)cols, (cuuint64_t)rows};
  cuuint64_t strides[1] = {(cuuint64_t)cols * 2};
  cuuint32_t box[2] = {(cuuint32_t)bc, (cuuint32_t)br}, es[2] = {1, 1};
  fn(m, CU_TENSOR_MAP_DATA_TYPE_BFLOAT16, 2, const_cast<void*>(p), dims, strides, box, es, CU_TENSOR_MAP_INTERLEAVE_NONE,
     bc == 64 ? CU_TENSOR_MAP_SWIZZLE_128B : bc == 32 ? CU_TENSOR_MAP_SWIZZLE_64B : CU_TENSOR_MAP_SWIZZLE_NONE,
     CU_TENSOR_MAP_L2_PROMOTION_L2_256B, CU_TENSOR_MAP_FLOAT_OOB_FILL_NONE);
}

}

extern "C" void kernel_launch(void* const* d_in, const int* in_sizes, int n_in, void* d_out, int out_size) {
  (void)in_sizes; (void)n_in; (void)out_size;
  const __nv_bfloat16* x = (const __nv_bfloat16*)d_in[0];
  const __nv_bfloat16* mem0 = (const __nv_bfloat16*)d_in[1];
  const __nv_bfloat16* Wq = (const __nv_bfloat16*)d_in[2];
  const __nv_bfloat16* Wk = (const __nv_bfloat16*)d_in[3];
  const __nv_bfloat16* Wv = (const __nv_bfloat16*)d_in[4];
  const __nv_bfloat16* Wo = (const __nv_bfloat16*)d_in[5];
  __nv_bfloat16* out = (__nv_bfloat16*)d_out;

  static EncodeFn enc = nullptr;
  if (!enc) {
    void* fn = nullptr; cudaDriverEntryPointQueryResult qr;
    cudaGetDriverEntryPoint("cuTensorMapEncodeTiled", &fn, cudaEnableDefault, &qr);
    enc = (EncodeFn)fn;
    cudaFuncSetAttribute(k_chain, cudaFuncAttributeMaxDynamicSharedMemorySize, SM_END);
    cudaFuncSetAttribute(k_help, cudaFuncAttributeMaxDynamicSharedMemorySize, G_SM_END);
  }
  CUtensorMap tmG, tmU, tmD, tmO;
  make_map(enc, &tmG, d_in[8], DM, FF);
  make_map(enc, &tmU, d_in[9], DM, FF);
  make_map(enc, &tmD, d_in[10], FF, DM);
  make_map(enc, &tmO, Wo, NH * DH, DM);
  WMaps wm;
  make_map(enc, &wm.q48, Wq, DM, NH * DH, 48, 64); make_map(enc, &wm.k48, Wk, DM, NH * DH, 48, 64);
  make_map(enc, &wm.q32, Wq, DM, NH * DH, 32, 64); make_map(enc, &wm.k32, Wk, DM, NH * DH, 32, 64);
  make_map(enc, &wm.v32, Wv, DM, NH * DH, 32, 64); make_map(enc, &wm.v64, Wv, DM, NH * DH, 64, 64);
  make_map(enc, &wm.o64, Wo, NH * DH, DM, 64, 64); make_map(enc, &wm.o32, Wo, NH * DH, DM, 32, 64);

  cudaStream_t st = cudaStreamPerThread;
  {
    cudaLaunchConfig_t cfg = {};
    cfg.gridDim = dim3(NCL * CLS); cfg.blockDim = dim3(512); cfg.dynamicSmemBytes = SM_END; cfg.stream = st;
    cudaLaunchAttribute at[1];
    at[0].id = cudaLaunchAttributeClusterDimension; at[0].val.clusterDim.x = CLS; at[0].val.clusterDim.y = 1; at[0].val.clusterDim.z = 1;
    cfg.attrs = at; cfg.numAttrs = 1;
    cudaLaunchKernelEx(&cfg, k_chain, wm, mem0, x);
  }
  {
    cudaLaunchConfig_t cfg = {};
    cfg.gridDim = dim3(NHELP); cfg.blockDim = dim3(384); cfg.dynamicSmemBytes = G_SM_END; cfg.stream = st;
    cudaLaunchAttribute at[1];
    at[0].id = cudaLaunchAttributeProgrammaticStreamSerialization; at[0].val.programmaticStreamSerializationAllowed = 1;
    cfg.attrs = at; cfg.numAttrs = 1;
    cudaLaunchKernelEx(&cfg, k_help, tmG, tmU, tmD, tmO, x, out);
  }
}
```
